```python
import torch

def _softmax(x, axis=-1):
    return torch.softmax(x, dim=axis)
def _gelu(x):
    return torch.nn.functional.gelu(x, approximate="tanh")
def _silu(x):
    return torch.nn.functional.silu(x)
def _sigmoid(x):
    return torch.sigmoid(x)
def _layernorm(x, axis=-1, eps=1e-5):
    m = x.mean(dim=axis, keepdim=True)
    v = x.var(dim=axis, keepdim=True, unbiased=False)
    return (x - m) / torch.sqrt(v + eps)
def _scatter_add(tgt, idx, src, axis=0):
    return tgt.clone().index_add_(axis, idx, src)
def _segment_sum(src, seg, n):
    out = torch.zeros((n,) + src.shape[1:], dtype=src.dtype)
    return out.index_add_(0, seg, src)
def _pad(x, pw):
    flat = tuple(v for pair in reversed(pw) for v in pair)
    return torch.nn.functional.pad(x, flat)

kernel_name = 'sequential_preLN__ssm_conv_s4d__geglu_ffn__prompt'

def setup_inputs():

    _w = (lambda a: (lambda t: t.to(torch.bfloat16) if t.is_floating_point() else t)(torch.as_tensor(a)))
    def _A_setup():
        Bsz, L, D, N = 1, 2048, 512, 128
        return {
            "u": _w((lambda *s: torch.randn(*s, dtype=torch.bfloat16) * 0.05)(Bsz, L, D)),
            "log_A_real": _w((lambda *s: torch.randn(*s, dtype=torch.bfloat16) * 6.4)(D, N) * 0.5),
            "A_imag": _w((lambda *s: torch.randn(*s, dtype=torch.bfloat16) * 0.05)(D, N) * 3.14),
            "C_real": _w((lambda *s: torch.randn(*s, dtype=torch.bfloat16) * 0.05)(D, N) / N ** 0.5),
            "C_imag": _w((lambda *s: torch.randn(*s, dtype=torch.bfloat16) * 0.05)(D, N) / N ** 0.5),
            "log_dt": _w((lambda *s: torch.randn(*s, dtype=torch.bfloat16) * 0.05)(D) * 0.5 - 4.0),
            "D_skip": _w((lambda *s: torch.randn(*s, dtype=torch.bfloat16) * 0.05)(D)),
        }
    _A_in = _A_setup()

    def _B_setup():
        B, S, D, F = 1, 2048, 512, 1376
        return {
            "x": _w((lambda *s: torch.randn(*s, dtype=torch.bfloat16) * 0.05)(B, S, D)),
            "w_gate": _w((lambda *s: torch.randn(*s, dtype=torch.bfloat16) * 0.05)(D, F)),
            "w_up": _w((lambda *s: torch.randn(*s, dtype=torch.bfloat16) * 0.05)(D, F)),
            "w_down": _w((lambda *s: torch.randn(*s, dtype=torch.bfloat16) * 0.05)(F, D)),
        }
    _B_in = _B_setup()

    return {
        "A_u": _A_in["u"],
        "A_log_A_real": _A_in["log_A_real"],
        "A_A_imag": _A_in["A_imag"],
        "A_C_real": _A_in["C_real"],
        "A_C_imag": _A_in["C_imag"],
        "A_log_dt": _A_in["log_dt"],
        "A_D_skip": _A_in["D_skip"],
        "B_x": _B_in["x"],
        "B_w_gate": _B_in["w_gate"],
        "B_w_up": _B_in["w_up"],
        "B_w_down": _B_in["w_down"],
    }

def reference(A_u, A_log_A_real, A_A_imag, A_C_real, A_C_imag, A_log_dt, A_D_skip, B_x, B_w_gate, B_w_up, B_w_down):
    def _A_ref(u, log_A_real, A_imag, C_real, C_imag, log_dt, D_skip):
        L = u.shape[1]
        dt = torch.exp(log_dt)
        A = -torch.exp(log_A_real) + 1j * A_imag
        C = (C_real + 1j * C_imag) * dt[:, None]
        pos = (lambda x, dt: x.to(dt))(torch.arange(L), log_dt.dtype)
        P = torch.exp((A * dt[:, None])[:, :, None] * pos[None, None, :])
        K = 2.0 * torch.einsum("dn,dnl->dl", C, P).real
        L2 = 2 * L
        u_t = (lambda x, *d: x.permute(*d))(u, 0, 2, 1)
        Kf = (lambda x, *a, **k: torch.fft.rfft(x.float(), *a, **k))(K, L2)
        Uf = (lambda x, *a, **k: torch.fft.rfft(x.float(), *a, **k))(u_t, L2)
        y = (lambda x, *a, **k: torch.fft.irfft(x, *a, **k).to(torch.bfloat16))(Uf * Kf[None, :, :], L2)[:, :, :L]
        y = (lambda x, *d: x.permute(*d))(y, 0, 2, 1)
        return y + u * D_skip[None, None, :]

    def _B_ref(x, w_gate, w_up, w_down):
        return (_gelu(x @ w_gate) * (x @ w_up)) @ w_down

    x = A_u
    h = x + _A_ref(_layernorm(x, axis=-1), A_log_A_real, A_A_imag, A_C_real, A_C_imag, A_log_dt, A_D_skip)
    h2 = h + _B_ref(_layernorm(h, axis=-1), B_w_gate, B_w_up, B_w_down)
    return h2
```

```cpp
#include <cuda_runtime.h>
#include <cuda_bf16.h>
#include <cuda_fp16.h>
#include <cuda.h>
#include <stdint.h>

#define SPIN_LIMIT 400000
__device__ __forceinline__ uint32_t s2u(const void* p) { return (uint32_t)__cvta_generic_to_shared(p); }
__device__ __forceinline__ void mbar_init(uint32_t b, uint32_t c) { asm volatile("mbarrier.init.shared::cta.b64 [%0], %1;" ::"r"(b), "r"(c) : "memory"); }
__device__ __forceinline__ void mbar_expect(uint32_t b, uint32_t tx) { asm volatile("mbarrier.arrive.expect_tx.shared::cta.b64 _, [%0], %1;" ::"r"(b), "r"(tx) : "memory"); }
__device__ __forceinline__ void mbar_arrive(uint32_t b) { asm volatile("mbarrier.arrive.shared::cta.b64 _, [%0];" ::"r"(b) : "memory"); }
__device__ __forceinline__ void mbar_wait(uint32_t b) {
    asm volatile("{ .reg .pred p; .reg .u32 it; mov.u32 it, 0;\n"
                 "W_LOOP: mbarrier.try_wait.parity.shared::cta.b64 p, [%0], 0;\n"
                 "@p bra W_DONE;\n add.u32 it, it, 1; setp.lt.u32 p, it, 200000; @p bra W_LOOP;\n"
                 "W_DONE: }" ::"r"(b) : "memory");
}
__device__ __forceinline__ void mbar_wait_cluster(uint32_t b) {
    asm volatile("{ .reg .pred p; .reg .u32 it; mov.u32 it, 0;\n"
                 "W_LOOP: mbarrier.try_wait.parity.acquire.cluster.shared::cta.b64 p, [%0], 0;\n"
                 "@p bra W_DONE;\n add.u32 it, it, 1; setp.lt.u32 p, it, 200000; @p bra W_LOOP;\n"
                 "W_DONE: }" ::"r"(b) : "memory");
}
__device__ __forceinline__ bool elect() { uint32_t p; asm volatile("{ .reg .pred P; elect.sync _|P, 0xffffffff; selp.u32 %0, 1, 0, P; }" : "=r"(p)); return p; }
__device__ __forceinline__ uint32_t mapa(uint32_t a, uint32_t r) { uint32_t o; asm volatile("mapa.shared::cluster.u32 %0, %1, %2;" : "=r"(o) : "r"(a), "r"(r)); return o; }
__device__ __forceinline__ void bulk_g2s(uint32_t dst, const void* g, uint32_t bytes, uint32_t bar) {
    asm volatile("cp.async.bulk.shared::cluster.global.mbarrier::complete_tx::bytes [%0], [%1], %2, [%3];" ::"r"(dst), "l"(g), "r"(bytes), "r"(bar) : "memory");
}
__device__ __forceinline__ void tma2d(uint32_t dst, const CUtensorMap* tm, uint32_t bar, int c0, int c1) {
    asm volatile("cp.async.bulk.tensor.2d.shared::cluster.global.mbarrier::complete_tx::bytes [%0], [%1, {%3, %4}], [%2];" ::"r"(dst), "l"(tm), "r"(bar), "r"(c0), "r"(c1) : "memory");
}
__device__ __forceinline__ void wg_fence() { asm volatile("wgmma.fence.sync.aligned;" ::: "memory"); }
__device__ __forceinline__ void wg_commit() { asm volatile("wgmma.commit_group.sync.aligned;" ::: "memory"); }
template <int N> __device__ __forceinline__ void wg_wait() { asm volatile("wgmma.wait_group.sync.aligned %0;" ::"n"(N) : "memory"); }
template <int N> __device__ __forceinline__ void pin(float (&d)[N]) {
#pragma unroll
    for (int i = 0; i < N; i++) asm volatile("" : "+f"(d[i])::"memory");
}
template <int N> __device__ __forceinline__ void pin(uint32_t (&d)[N]) {
#pragma unroll
    for (int i = 0; i < N; i++) asm volatile("" : "+r"(d[i])::"memory");
}
__device__ __forceinline__ void ldsm4t(uint32_t& r0, uint32_t& r1, uint32_t& r2, uint32_t& r3, uint32_t a) {
    asm volatile("ldmatrix.sync.aligned.m8n8.x4.trans.shared.b16 {%0,%1,%2,%3}, [%4];" : "=r"(r0), "=r"(r1), "=r"(r2), "=r"(r3) : "r"(a) : "memory");
}
__device__ __forceinline__ void stsm4(uint32_t a, uint32_t r0, uint32_t r1, uint32_t r2, uint32_t r3) {
    asm volatile("stmatrix.sync.aligned.m8n8.x4.shared.b16 [%0], {%1,%2,%3,%4};" ::"r"(a), "r"(r0), "r"(r1), "r"(r2), "r"(r3) : "memory");
}
__device__ __forceinline__ uint32_t pack_bf16(float lo, float hi) { uint32_t r; asm("cvt.rn.bf16x2.f32 %0, %1, %2;" : "=r"(r) : "f"(hi), "f"(lo)); return r; }
__device__ __forceinline__ uint32_t pack_f16(float lo, float hi) { uint32_t r; asm("cvt.rn.f16x2.f32 %0, %1, %2;" : "=r"(r) : "f"(hi), "f"(lo)); return r; }
__device__ __forceinline__ float bf_lo(uint32_t v) { return __uint_as_float(v << 16); }
__device__ __forceinline__ float bf_hi(uint32_t v) { return __uint_as_float(v & 0xffff0000u); }
__device__ __forceinline__ float rbf(float x) { return __uint_as_float(pack_bf16(0.f, x)); }
__device__ __forceinline__ uint32_t ld_relaxed(const uint32_t* p) { uint32_t v; asm volatile("ld.relaxed.gpu.global.u32 %0, [%1];" : "=r"(v) : "l"(p) : "memory"); return v; }
__device__ __forceinline__ void red_release(uint32_t* p, uint32_t v) { asm volatile("red.release.gpu.global.add.u32 [%0], %1;" ::"l"(p), "r"(v) : "memory"); }
__device__ __forceinline__ void fence_async_global() { asm volatile("fence.proxy.async.global;" ::: "memory"); }
__device__ __forceinline__ void fence_async_smem() { asm volatile("fence.proxy.async.shared::cta;" ::: "memory"); }
template <uint32_t HA, uint32_t HB, int ACC>
__device__ __forceinline__ void wg128_ss_tn(float (&d)[64], uint32_t la, uint32_t lb) {
    asm volatile("{ .reg .pred p; .reg .b64 da, db; setp.ne.b32 p, %68, 0; mov.b64 da, {%64, %66}; mov.b64 db, {%65, %67};\n"
        "wgmma.mma_async.sync.aligned.m64n128k16.f32.bf16.bf16 "
        "{%0, %1, %2, %3, %4, %5, %6, %7, %8, %9, %10, %11, %12, %13, %14, %15, %16, %17, %18, %19, %20, %21, %22, %23, %24, %25, %26, %27, %28, %29, %30, %31, %32, %33, %34, %35, %36, %37, %38, %39, %40, %41, %42, %43, %44, %45, %46, %47, %48, %49, %50, %51, %52, %53, %54, %55, %56, %57, %58, %59, %60, %61, %62, %63}, da, db, p, 1, 1, 1, 0; }"
        : "+f"(d[0]), "+f"(d[1]), "+f"(d[2]), "+f"(d[3]), "+f"(d[4]), "+f"(d[5]), "+f"(d[6]), "+f"(d[7]), "+f"(d[8]), "+f"(d[9]), "+f"(d[10]), "+f"(d[11]), "+f"(d[12]), "+f"(d[13]), "+f"(d[14]), "+f"(d[15]), "+f"(d[16]), "+f"(d[17]), "+f"(d[18]), "+f"(d[19]), "+f"(d[20]), "+f"(d[21]), "+f"(d[22]), "+f"(d[23]), "+f"(d[24]), "+f"(d[25]), "+f"(d[26]), "+f"(d[27]), "+f"(d[28]), "+f"(d[29]), "+f"(d[30]), "+f"(d[31]), "+f"(d[32]), "+f"(d[33]), "+f"(d[34]), "+f"(d[35]), "+f"(d[36]), "+f"(d[37]), "+f"(d[38]), "+f"(d[39]), "+f"(d[40]), "+f"(d[41]), "+f"(d[42]), "+f"(d[43]), "+f"(d[44]), "+f"(d[45]), "+f"(d[46]), "+f"(d[47]), "+f"(d[48]), "+f"(d[49]), "+f"(d[50]), "+f"(d[51]), "+f"(d[52]), "+f"(d[53]), "+f"(d[54]), "+f"(d[55]), "+f"(d[56]), "+f"(d[57]), "+f"(d[58]), "+f"(d[59]), "+f"(d[60]), "+f"(d[61]), "+f"(d[62]), "+f"(d[63])
        : "r"(la), "r"(lb), "n"(HA), "n"(HB), "n"(ACC));
}
template <uint32_t HA, uint32_t HB, int ACC>
__device__ __forceinline__ void wg96_ss_tn(float (&d)[48], uint32_t la, uint32_t lb) {
    asm volatile("{ .reg .pred p; .reg .b64 da, db; setp.ne.b32 p, %52, 0; mov.b64 da, {%48, %50}; mov.b64 db, {%49, %51};\n"
        "wgmma.mma_async.sync.aligned.m64n96k16.f32.bf16.bf16 "
        "{%0, %1, %2, %3, %4, %5, %6, %7, %8, %9, %10, %11, %12, %13, %14, %15, %16, %17, %18, %19, %20, %21, %22, %23, %24, %25, %26, %27, %28, %29, %30, %31, %32, %33, %34, %35, %36, %37, %38, %39, %40, %41, %42, %43, %44, %45, %46, %47}, da, db, p, 1, 1, 1, 0; }"
        : "+f"(d[0]), "+f"(d[1]), "+f"(d[2]), "+f"(d[3]), "+f"(d[4]), "+f"(d[5]), "+f"(d[6]), "+f"(d[7]), "+f"(d[8]), "+f"(d[9]), "+f"(d[10]), "+f"(d[11]), "+f"(d[12]), "+f"(d[13]), "+f"(d[14]), "+f"(d[15]), "+f"(d[16]), "+f"(d[17]), "+f"(d[18]), "+f"(d[19]), "+f"(d[20]), "+f"(d[21]), "+f"(d[22]), "+f"(d[23]), "+f"(d[24]), "+f"(d[25]), "+f"(d[26]), "+f"(d[27]), "+f"(d[28]), "+f"(d[29]), "+f"(d[30]), "+f"(d[31]), "+f"(d[32]), "+f"(d[33]), "+f"(d[34]), "+f"(d[35]), "+f"(d[36]), "+f"(d[37]), "+f"(d[38]), "+f"(d[39]), "+f"(d[40]), "+f"(d[41]), "+f"(d[42]), "+f"(d[43]), "+f"(d[44]), "+f"(d[45]), "+f"(d[46]), "+f"(d[47])
        : "r"(la), "r"(lb), "n"(HA), "n"(HB), "n"(ACC));
}
template <uint32_t HB, int ACC>
__device__ __forceinline__ void wg128_rs_t(float (&d)[64], uint32_t a0, uint32_t a1, uint32_t a2, uint32_t a3, uint32_t lb) {
    asm volatile("{ .reg .pred p; .reg .b64 db; setp.ne.b32 p, %70, 0; mov.b64 db, {%68, %69};\n"
        "wgmma.mma_async.sync.aligned.m64n128k16.f32.bf16.bf16 "
        "{%0, %1, %2, %3, %4, %5, %6, %7, %8, %9, %10, %11, %12, %13, %14, %15, %16, %17, %18, %19, %20, %21, %22, %23, %24, %25, %26, %27, %28, %29, %30, %31, %32, %33, %34, %35, %36, %37, %38, %39, %40, %41, %42, %43, %44, %45, %46, %47, %48, %49, %50, %51, %52, %53, %54, %55, %56, %57, %58, %59, %60, %61, %62, %63}, {%64, %65, %66, %67}, db, p, 1, 1, 1; }"
        : "+f"(d[0]), "+f"(d[1]), "+f"(d[2]), "+f"(d[3]), "+f"(d[4]), "+f"(d[5]), "+f"(d[6]), "+f"(d[7]), "+f"(d[8]), "+f"(d[9]), "+f"(d[10]), "+f"(d[11]), "+f"(d[12]), "+f"(d[13]), "+f"(d[14]), "+f"(d[15]), "+f"(d[16]), "+f"(d[17]), "+f"(d[18]), "+f"(d[19]), "+f"(d[20]), "+f"(d[21]), "+f"(d[22]), "+f"(d[23]), "+f"(d[24]), "+f"(d[25]), "+f"(d[26]), "+f"(d[27]), "+f"(d[28]), "+f"(d[29]), "+f"(d[30]), "+f"(d[31]), "+f"(d[32]), "+f"(d[33]), "+f"(d[34]), "+f"(d[35]), "+f"(d[36]), "+f"(d[37]), "+f"(d[38]), "+f"(d[39]), "+f"(d[40]), "+f"(d[41]), "+f"(d[42]), "+f"(d[43]), "+f"(d[44]), "+f"(d[45]), "+f"(d[46]), "+f"(d[47]), "+f"(d[48]), "+f"(d[49]), "+f"(d[50]), "+f"(d[51]), "+f"(d[52]), "+f"(d[53]), "+f"(d[54]), "+f"(d[55]), "+f"(d[56]), "+f"(d[57]), "+f"(d[58]), "+f"(d[59]), "+f"(d[60]), "+f"(d[61]), "+f"(d[62]), "+f"(d[63])
        : "r"(a0), "r"(a1), "r"(a2), "r"(a3), "r"(lb), "n"(HB), "n"(ACC));
}
template <uint32_t HB, int ACC>
__device__ __forceinline__ void wg64_rs_t(float (&d)[32], uint32_t a0, uint32_t a1, uint32_t a2, uint32_t a3, uint32_t lb) {
    asm volatile("{ .reg .pred p; .reg .b64 db; setp.ne.b32 p, %38, 0; mov.b64 db, {%36, %37};\n"
        "wgmma.mma_async.sync.aligned.m64n64k16.f32.bf16.bf16 "
        "{%0, %1, %2, %3, %4, %5, %6, %7, %8, %9, %10, %11, %12, %13, %14, %15, %16, %17, %18, %19, %20, %21, %22, %23, %24, %25, %26, %27, %28, %29, %30, %31}, {%32, %33, %34, %35}, db, p, 1, 1, 1; }"
        : "+f"(d[0]), "+f"(d[1]), "+f"(d[2]), "+f"(d[3]), "+f"(d[4]), "+f"(d[5]), "+f"(d[6]), "+f"(d[7]), "+f"(d[8]), "+f"(d[9]), "+f"(d[10]), "+f"(d[11]), "+f"(d[12]), "+f"(d[13]), "+f"(d[14]), "+f"(d[15]), "+f"(d[16]), "+f"(d[17]), "+f"(d[18]), "+f"(d[19]), "+f"(d[20]), "+f"(d[21]), "+f"(d[22]), "+f"(d[23]), "+f"(d[24]), "+f"(d[25]), "+f"(d[26]), "+f"(d[27]), "+f"(d[28]), "+f"(d[29]), "+f"(d[30]), "+f"(d[31])
        : "r"(a0), "r"(a1), "r"(a2), "r"(a3), "r"(lb), "n"(HB), "n"(ACC));
}

typedef __nv_bfloat16 bf16;
constexpr int F_ = 1376;
constexpr int SLOT = 16384;
constexpr int CHUNK_BYTES = 2 * 8 * 16384 + 8 * 12288;
#define GRIDN 132
constexpr int GRID = GRIDN;

struct Scratch {
    unsigned char hT[16 * 8 * SLOT];
    unsigned char w1p[8 * CHUNK_BYTES];
    uint4 act[128][11][256];
    float2 stat[2048];
    uint32_t hcnt[16][32];
    uint32_t acthint[32][8][4];
    uint32_t claim[64];
    uint32_t nstart[32];
    uint32_t wcnt[8][32];
};
__device__ __align__(1024) Scratch g_scr;

__host__ __device__ constexpr int chan_of_k(int k) { return (((k ^ (k >> 8 << 2)) & 255) >> 1) * 4 + (k >> 8) * 2 + (k & 1); }

#define SCHED0 0x44332211u
#define SCHED1 0x54433211u
#define SCHED2 0x211000u
__host__ __device__ constexpr int fcol(int j, int p) { return p < 2 ? 128 * j + 64 * p : 1024 + 176 * (j >> 2) + 48 * (j & 3); }
#define EXTRA_DELAY 5000
#define XDELAY 100
#define NPRE 4
#define ALEAD 6
#define CREGS 232
#define FORCE_REDO 0
#define CV 3
#define RES_STEP 11
#define RECV_STEP 12
constexpr int SM_CS = 14 * SLOT;
constexpr int SM_MISC = SM_CS + 1024;
constexpr int SM_BAR = SM_MISC + 16;
constexpr int B_FULL = 0  , B_XREADY = 36, B_XFULL = 37  , B_CS = 38, B_DONE = 40  , B_STORED = 72  , B_PREP = 75, B_KALU = 76,
              B_CONV = 77  , B_ORDER = 80  , B_ROW = 88, B_X = 89, B_GT = 90, B_PAR = 91, B_W = 92, B_ROLE = 93, B_COUNT = 96;
constexpr int SMEM_BYTES = SM_BAR + B_COUNT * 8;
constexpr int CV_U = 384, CV_X = 4608, CV_TAB = 8704, CV_KD = CV_TAB + 4096, CV_PAR = CV_KD + 1792;
constexpr int T_NEAR = CV_TAB + 8 * 4, T_G2A = CV_TAB + (544 - 48) * 4, T_G3A = CV_TAB + (544 + 192 - 112) * 4;
static_assert(CV_PAR + 1056 <= SLOT, "conv area");

struct GTab { uint32_t epoch, pad[3]; uint16_t v[64][24]; uint32_t band[32][8]; };
constexpr int tap_index(int lag) {
    if (lag <= 256) return lag;
    const int sh = lag < 512 ? 1 : (lag < 1024 ? 2 : 3);
    int q = lag >> sh;
    const int rem = lag & ((1 << sh) - 1), h = 1 << (sh - 1);
    if (rem > h || (rem == h && (q & 1))) q++;
    return q + 128 * sh;
}
constexpr int KD_PITCH = 52, KD_ZERO = 32 * KD_PITCH;
constexpr GTab make_gtab() {
    GTab t{};
    for (int tt = 0; tt < 64; tt++)
        for (int g = 0; g < 4; g++) {
            const int en = (g * 64 + tt) * 4;
            int lag0 = 0, step = 8, lo = 0, hi = 0;
            if (en < 544) { lag0 = en - 8; step = 1; lo = 0; hi = 514; }
            else if (en < 640) { lag0 = (en - 544 + 48) * 8 + 4; lo = 516; hi = 1020; }
            else if (en < 736) { lag0 = (en - 640 + 48) * 8 + 8; lo = 520; hi = 1024; }
            else if (en < 880) { lag0 = (en - 736 + 112) * 8 + 4; lo = 1028; hi = 2044; }
            else { lag0 = (en - 880 + 112) * 8 + 8; lo = 1032; hi = 2048; }
            for (int e = 0; e < 5; e++) {
                const int lag = lag0 + (e - 1) * step;
                int off = KD_ZERO;
                if (lag >= lo && lag <= hi) {
                    const int ti = tap_index(lag);
                    const int pos = ti <= 256 ? ti : (ti < 384 ? (ti - 128) * 2 : (ti < 512 ? (ti - 256) * 4 : (ti - 384) * 8));
                    int col = 0;
                    if (pos < 256) col = pos & 7;
                    else if (pos < 512) col = 8 + (pos & 7);
                    else if ((pos & 7) == 4) col = pos < 768 ? 9 : 11;
                    else col = 16 + (pos >> 8) - 1;
                    off = ((pos & 255) >> 3) * KD_PITCH + col * 2;
                }
                t.v[tt][g * 5 + e] = (uint16_t)off;
            }
        }
    for (int lane = 0; lane < 32; lane++)
        for (int r = 0; r < 8; r++) {
            const int base = r < 4 ? 10 : 12, lo = r < 4 ? ((r & 1) ? 6 : 3) : ((r & 1) ? 5 : 4), hi = r < 4 ? ((r & 1) ? 10 : 5) : ((r & 1) ? 11 : 4);
            const int l = (lane >> 2) - 2 * (lane & 3) + base - ((r & 2) ? 8 : 0);
            t.band[lane][r] = ((l >= lo && l <= hi) ? 0x3c00u : 0u) | ((l - 1 >= lo && l - 1 <= hi) ? 0x3c000000u : 0u);
        }
    return t;
}
__device__ __align__(128) GTab g_gtab = make_gtab();
constexpr int SM_GT = 14 * SLOT - 5120, GT_V = SM_GT + 16, GT_BAND = GT_V + 3072;
constexpr int KD_1024 = 2 * (16 + 3);

struct RowC { float k1, k3; };
__device__ __forceinline__ float geglu(float g, float u, const RowC& c) {
    float p = fmaf(g * g, c.k3, c.k1), th;
    asm("tanh.approx.f32 %0, %1;" : "=f"(th) : "f"(p * g));
    float gu = g * u;
    return fmaf(gu, th, gu);
}
template <int NG, int NA>
__device__ __forceinline__ void geglu_group(float (&acc)[NA], int q, const RowC& c0, const RowC& c1, uint32_t& o0, uint32_t& o1) {
    asm volatile("" : "+f"(acc[4 * q]), "+f"(acc[4 * q + 1]), "+f"(acc[4 * q + 2]), "+f"(acc[4 * q + 3])::"memory");
    o0 = pack_bf16(geglu(acc[4 * q + 0], acc[4 * (q + NG) + 0], c0), geglu(acc[4 * q + 1], acc[4 * (q + NG) + 1], c0));
    o1 = pack_bf16(geglu(acc[4 * q + 2], acc[4 * (q + NG) + 2], c1), geglu(acc[4 * q + 3], acc[4 * (q + NG) + 3], c1));
}
template <int N>
__device__ __forceinline__ void stats_acc(const uint32_t (&a)[N], float& s0, float& q0, float& s1, float& q1) {
#pragma unroll
    for (int i = 0; i < N; i += 2) {
        float x0 = bf_lo(a[i]), x1 = bf_hi(a[i]), y0 = bf_lo(a[i + 1]), y1 = bf_hi(a[i + 1]);
        s0 += x0 + x1; q0 = fmaf(x0, x0, q0); q0 = fmaf(x1, x1, q0);
        s1 += y0 + y1; q1 = fmaf(y0, y0, q1); q1 = fmaf(y1, y1, q1);
    }
}
__device__ __forceinline__ uint32_t tag_bad(uint32_t a, uint32_t b, uint32_t c, uint32_t d, uint32_t tag) {
    uint32_t x, y;
    asm("lop3.b32 %0, %1, %2, %3, 0x7e;" : "=r"(x) : "r"(a), "r"(b), "r"(tag));
    asm("lop3.b32 %0, %1, %2, %3, 0x7e;" : "=r"(y) : "r"(c), "r"(d), "r"(tag));
    return (x | y) & 1;
}
__device__ __forceinline__ void ln_finish(float s, float q, RowC& c, float& sc) {
    float m = s * (1.0f / 512);
    float v = fmaxf(fmaf(-m, m, q * (1.0f / 512)), 0.0f) + 1e-5f;
    float r; asm("rsqrt.approx.ftz.f32 %0, %1;" : "=f"(r) : "f"(v));
    c.k1 = 0.7978845608f * r;
    sc = 0.5f * r * r;
    c.k3 = (2.0f * 0.044715f) * c.k1 * sc;
}
constexpr uint32_t HI_SW128 = 0x40000000u | (1024 >> 4);
constexpr uint32_t HI_NOSW = (1024 >> 4);
__device__ __forceinline__ uint32_t desc_lo(uint32_t addr, uint32_t lbo) { return ((addr & 0x3FFFF) >> 4) | ((lbo >> 4) << 16); }


__device__ __forceinline__ void mma_f32(float (&d)[4], uint32_t a0, uint32_t a1, uint32_t a2, uint32_t a3, uint32_t b0, uint32_t b1) {
    asm("mma.sync.aligned.m16n8k16.row.col.f32.f16.f16.f32 {%0,%1,%2,%3}, {%4,%5,%6,%7}, {%8,%9}, {%0,%1,%2,%3};"
        : "+f"(d[0]), "+f"(d[1]), "+f"(d[2]), "+f"(d[3]) : "r"(a0), "r"(a1), "r"(a2), "r"(a3), "r"(b0), "r"(b1));
}
__device__ __forceinline__ void mma_f16(uint32_t& d0, uint32_t& d1, const uint32_t (&a)[4], uint32_t b0, uint32_t b1) {
    asm("mma.sync.aligned.m16n8k16.row.col.f16.f16.f16.f16 {%0,%1}, {%2,%3,%4,%5}, {%6,%7}, {%8,%8};"
        : "=r"(d0), "=r"(d1) : "r"(a[0]), "r"(a[1]), "r"(a[2]), "r"(a[3]), "r"(b0), "r"(b1), "r"(0u));
}
__device__ __forceinline__ uint32_t lds32(uint32_t a) { uint32_t v; asm volatile("ld.shared.u32 %0, [%1];" : "=r"(v) : "r"(a)); return v; }
__device__ __forceinline__ uint32_t lds16(uint32_t a) { uint16_t v; asm volatile("ld.shared.u16 %0, [%1];" : "=h"(v) : "r"(a)); return v; }
__device__ __forceinline__ void sts32(uint32_t a, uint32_t v) { asm volatile("st.shared.u32 [%0], %1;" ::"r"(a), "r"(v) : "memory"); }
__device__ __forceinline__ void sts64(uint32_t a, uint32_t x, uint32_t y) { asm volatile("st.shared.v2.u32 [%0], {%1,%2};" ::"r"(a), "r"(x), "r"(y) : "memory"); }
__device__ __forceinline__ void sts128(uint32_t a, uint32_t x, uint32_t y, uint32_t z, uint32_t w) { asm volatile("st.shared.v4.u32 [%0], {%1,%2,%3,%4};" ::"r"(a), "r"(x), "r"(y), "r"(z), "r"(w) : "memory"); }
__device__ __forceinline__ void ldsm4n(uint32_t (&r)[4], uint32_t a) {
    asm volatile("ldmatrix.sync.aligned.m8n8.x4.shared.b16 {%0,%1,%2,%3}, [%4];" : "=r"(r[0]), "=r"(r[1]), "=r"(r[2]), "=r"(r[3]) : "r"(a));
}
__device__ __forceinline__ void bar_sync(int id, int n) { asm volatile("bar.sync %0, %1;" ::"r"(id), "r"(n) : "memory"); }
__device__ __forceinline__ uint4 ld_relaxed4(const void* p) {
    uint4 v; asm volatile("ld.relaxed.gpu.global.v4.u32 {%0,%1,%2,%3}, [%4];" : "=r"(v.x), "=r"(v.y), "=r"(v.z), "=r"(v.w) : "l"(p) : "memory"); return v;
}
__device__ __forceinline__ void mbar_arrive2(uint32_t b) { asm volatile("mbarrier.arrive.shared::cta.b64 _, [%0], 2;" ::"r"(b) : "memory"); }
__device__ __forceinline__ void mbar_arrive_pair(uint32_t b2) { asm volatile("mbarrier.arrive.shared::cluster.b64 _, [%0];" ::"r"(b2) : "memory"); }
__device__ __forceinline__ void st_relaxed4(void* p, uint32_t x, uint32_t y, uint32_t z, uint32_t w) {
    asm volatile("{ .reg .b64 a, b; .reg .b128 v; mov.b64 a, {%1,%2}; mov.b64 b, {%3,%4}; mov.b128 v, {a, b}; st.relaxed.gpu.global.b128 [%0], v; }" ::"l"(p), "r"(x), "r"(y), "r"(z), "r"(w) : "memory");
}
__device__ __forceinline__ uint4 ld_relaxed128(const void* p) {
    uint4 v;
    asm volatile("{ .reg .b64 a, b; .reg .b128 v; ld.relaxed.gpu.global.b128 v, [%4]; mov.b128 {a, b}, v; mov.b64 {%0,%1}, a; mov.b64 {%2,%3}, b; }" : "=r"(v.x), "=r"(v.y), "=r"(v.z), "=r"(v.w) : "l"(p) : "memory");
    return v;
}
__device__ __forceinline__ uint4 ld_relaxed2x64(const void* p) {
    uint4 v;
    asm volatile("{ .reg .b64 a, b; ld.relaxed.gpu.global.v2.b64 {a, b}, [%4]; mov.b64 {%0,%1}, a; mov.b64 {%2,%3}, b; }" : "=r"(v.x), "=r"(v.y), "=r"(v.z), "=r"(v.w) : "l"(p) : "memory");
    return v;
}
__device__ __forceinline__ void init_bars(uint32_t bar, int warp) {
    if (elect()) {
        const uint32_t cnt = (warp >= 5 && warp < 10) ? 8 : 1;
#pragma unroll
        for (int i = 0; i < 8; i++) mbar_init(bar + warp * 64 + i * 8, cnt);
        asm volatile("fence.mbarrier_init.release.cluster;" ::: "memory");
    }
    __syncwarp();
    asm volatile("barrier.cluster.arrive.relaxed.aligned;" ::: "memory");
}
__device__ __forceinline__ uint32_t hcmul(uint32_t v, uint32_t m, uint32_t mr) {
    const __half2 h = *(const __half2*)&v;
    const __half2 r = __hfma2(__low2half2(h), *(const __half2*)&m, __hmul2(__high2half2(h), *(const __half2*)&mr));
    return *(const uint32_t*)&r;
}
struct cf { float x, y; };
__device__ __forceinline__ cf cmul(cf a, cf b) { return {fmaf(a.x, b.x, -a.y * b.y), fmaf(a.x, b.y, a.y * b.x)}; }
__device__ __forceinline__ cf csq(cf a, float two) { return {fmaf(a.x, a.x, -a.y * a.y), two * a.x * a.y}; }
__device__ __forceinline__ cf cpow(float al2, float om, float p) {
    float e; asm("ex2.approx.ftz.f32 %0, %1;" : "=f"(e) : "f"(al2 * p));
    float ph = om * p;
    return {e * __cosf(ph), e * __sinf(ph)};
}
__device__ __forceinline__ uint32_t lds32n(uint32_t a) { uint32_t v; asm("ld.shared.u32 %0, [%1];" : "=r"(v) : "r"(a)); return v; }
__device__ __forceinline__ void ldsm4nn(uint32_t (&r)[4], uint32_t a) {
    asm("ldmatrix.sync.aligned.m8n8.x4.shared.b16 {%0,%1,%2,%3}, [%4];" : "=r"(r[0]), "=r"(r[1]), "=r"(r[2]), "=r"(r[3]) : "r"(a));
}

#define SPLIT 10
template <int T0, int NT>
__device__ __forceinline__ void conv_tiles(uint32_t cv, int lane, uint32_t release_bar, const uint32_t (&band2)[4], const uint32_t (&band3)[4],
                                           unsigned char* hp, float kscale) {
    const uint32_t tl = cv + ((lane >> 2) - 2 * (lane & 3)) * 4;
    const uint32_t xl = cv + CV_U + (((lane >> 3) & 1) * 8 + (lane >> 4) + (lane & 7)) * 16;
    const uint32_t ul = cv + CV_U + lane * 4;
    constexpr int T1 = T0 + NT;
    float acc[NT][4], sh[NT + 1][4];
#pragma unroll
    for (int A = 0; A <= NT; A++) sh[A][0] = sh[A][1] = sh[A][2] = sh[A][3] = 0.f;
#pragma unroll
    for (int A = 0; A < NT; A++) acc[A][0] = acc[A][1] = acc[A][2] = acc[A][3] = 0.f;
    if (T1 > 8) {
        const uint32_t kv = lds32n(cv + CV_KD + KD_1024 - 2) >> 16;
        const int d = (lane >> 2) + 5 - 2 * (lane & 3);
        const uint32_t b0 = d == 0 ? kv : (d == 1 ? kv << 16 : 0u), b1 = d == 8 ? kv : (d == 9 ? kv << 16 : 0u);
#pragma unroll
        for (int A = T0; A < T1; A++) if (A >= 8) { uint32_t q[4]; ldsm4nn(q, xl + (16 * (A - 8) - 1) * 16); mma_f32(acc[A - T0], q[0], q[1], q[2], q[3], b0, b1); }
    }
#pragma unroll 1
    for (int par = 0; par < 2; par++) {
        const uint32_t up_ = ul + par * 128, tp = tl - par * 32;
        uint32_t w0[12], w1[12], y0[8], y1[8];
#pragma unroll
        for (int i = 0; i < 12; i++) if (i >= T0 - 8 && i < T1 - 4) { const uint32_t a = up_ + i * 256 - 20; mma_f16(w0[i], w1[i], band2, lds32n(a), lds32n(a + 16)); }
#pragma unroll
        for (int i = 0; i < 8; i++) if (i < T1 - 8) { const uint32_t a = up_ + i * 256 - 24; mma_f16(y0[i], y1[i], band3, lds32n(a), lds32n(a + 16)); }
#pragma unroll
        for (int n = 0; n < 8; n++) {
            if (n < 5 && n < T1 - 4) {
                const uint32_t a = tp + T_G2A + (8 + 2 * n) * 32;
                const uint32_t a0 = lds32n(a), a1 = lds32n(a + 32), a2 = lds32n(a + 384), a3 = lds32n(a + 416);
#pragma unroll
                for (int A = T1 - 1; A >= T0; A--) if (A - 4 - n >= 0) mma_f32(acc[A - T0], a0, a1, a2, a3, w0[(A + 8 - n) % 12], w1[(A + 8 - n) % 12]);
            }
            const int i = n < 5 ? 7 - n : n - 5;
            if (i < T1 - 8) {
                const uint32_t a = tp + T_G3A + (16 + 2 * i) * 32;
                const uint32_t a0 = lds32n(a), a1 = lds32n(a + 32), a2 = lds32n(a + 576), a3 = lds32n(a + 608);
#pragma unroll
                for (int A = T1 - 1; A >= T0; A--) if (A - 8 - i >= 0) mma_f32(acc[A - T0], a0, a1, a2, a3, y0[(A - i) % 8], y1[(A - i) % 8]);
            }
        }
    }
    const uint32_t xb = xl + T0 * 256 - 65 * 16, tn = tl + T_NEAR + 32;
#pragma unroll
    for (int jj = 0; jj < 4; jj++) {
        uint32_t r[9][2];
#pragma unroll
        for (int v = 0; v < 9; v++) { r[v][0] = lds32n(tn + jj * 64 + v * 256); r[v][1] = lds32n(tn + jj * 64 + v * 256 - 32); }
#pragma unroll
        for (int i = (T0 ? 0 : 4); i < NT + 4; i++) {
            uint32_t q[4];
            ldsm4nn(q, xb - jj * 32 + i * 256);
#pragma unroll
            for (int v = 0; v < 9; v++) {
                const int blk = 2 * i - 8 + v;
                if (blk >= -1 && blk < 2 * NT && (v < 8 || jj == 0)) {
                    if (v & 1) mma_f32(sh[(blk + 1) / 2], q[0], q[1], q[2], q[3], r[v][0], r[v][1]);
                    else mma_f32(acc[blk / 2], q[0], q[1], q[2], q[3], r[v][0], r[v][1]);
                }
            }
        }
    }
    if (lane == 0) mbar_arrive(release_bar);
    const uint32_t ks2 = pack_bf16(kscale, kscale);
#pragma unroll
    for (int i = 0; i < 8; i++) {
        uint32_t x[4];
        asm("ld.shared.v4.u32 {%0,%1,%2,%3}, [%4];" : "=r"(x[0]), "=r"(x[1]), "=r"(x[2]), "=r"(x[3]) : "r"(cv + CV_X + i * 512 + lane * 16));
#pragma unroll
        for (int q = 0; q < 4; q++) {
            const int H = i + 8 * q, A = H / 2 - T0;
            if (A >= 0 && A < NT) {
                const int a = A >= 0 && A < NT ? A : 0;
                const uint32_t z = (H & 1) ? pack_bf16(acc[a][2] + sh[a + 1][0], acc[a][3] + sh[a + 1][1]) : pack_bf16(acc[a][0] + sh[a][2], acc[a][1] + sh[a][3]);
                uint32_t h;
                asm("fma.rn.bf16x2 %0, %1, %2, %3;" : "=r"(h) : "r"(z), "r"(ks2), "r"(x[q]));
                *(uint32_t*)(hp + (H / 2) * 8 * SLOT + (H & 1) * 8192) = h;
            }
        }
    }
}

__device__ __forceinline__ int preferred_slot() {
    unsigned smid; asm volatile("mov.u32 %0, %%smid;" : "=r"(smid));
    const int tp = smid >> 1, t7 = (tp - 32) / 7;
    int slot = (tp & 7) * 8 + (tp >> 3);
    if (tp >= 32) slot = (1 + tp - 32 - 7 * t7) * 8 + 4 + t7;
    if (tp >= 60) slot = (tp < 62 || tp >= 66) ? -1 : tp - 58;
    return slot;
}
#define FFN_ROLE() mbar_wait_cluster(bar + B_ROLE * 8); \
    const int slot_id = __shfl_sync(0xffffffffu, (int)lds32(sb + SM_MISC), 0); \
    const int rb = ((slot_id >> 4) << 2) + (slot_id & 3), cb = (slot_id >> 2) & 3, j = rank * 4 + cb
__device__ __forceinline__ uint32_t clk32() { uint32_t t; asm volatile("mov.u32 %0, %%clock;" : "=r"(t)::"memory"); return t; }
__device__ __forceinline__ void mma_bf16(float (&d)[4], uint32_t a0, uint32_t a1, uint32_t a2, uint32_t a3, uint32_t b0, uint32_t b1) {
    asm("mma.sync.aligned.m16n8k16.row.col.f32.bf16.bf16.f32 {%0,%1,%2,%3}, {%4,%5,%6,%7}, {%8,%9}, {%0,%1,%2,%3};"
        : "+f"(d[0]), "+f"(d[1]), "+f"(d[2]), "+f"(d[3]) : "r"(a0), "r"(a1), "r"(a2), "r"(a3), "r"(b0), "r"(b1));
}
__device__ __forceinline__ void load_unit(int u, uint32_t dst, uint32_t wbar, const CUtensorMap* tg, const CUtensorMap* tu) {
    mbar_expect(wbar, 32768);
    asm volatile("cp.async.bulk.tensor.4d.shared::cluster.global.mbarrier::complete_tx::bytes [%0], [%1, {%3, %4, %4, %4}], [%2];"
                 ::"r"(dst), "l"((u & 1) ? tu : tg), "r"(wbar), "r"((u >> 1) * 32), "r"(0) : "memory");
}
__device__ __forceinline__ void pack_unit(Scratch* S, int u, uint32_t base, uint32_t red, uint32_t wbar, uint32_t gate, int bar_id, int pw, int lane, uint32_t sb) {
    const uint32_t row = lane ^ ((pw & 2) << 1), so = base + pw * 8192, stg = so + row * 64, sw = ((row >> 1) & 3) << 4;
    const int q16 = (u >> 1) * 2 + (lane & 1), r = q16 - 64, h = r >= 11, cb = ((r - 11 * h) * 11) >> 5;
    const int j = r < 0 ? q16 >> 3 : 4 * h + cb, p = r < 0 ? (q16 >> 2) & 1 : 2, half = r < 0 ? 8192 : 6144;
    uint32_t off = j * CHUNK_BYTES + p * 131072 + (r < 0 ? q16 & 3 : r - 11 * h - 3 * cb) * 2048 + (pw * 4 + (lane & 2) + (u & 1)) * half;
    if (lane & 4) off = r - 11 * h == 10 ? off + 2048 : ~0u;
    mbar_wait(wbar);
    uint32_t a[4][4][4];
    float cs[4][4];
#pragma unroll
    for (int i = 0; i < 4; i++)
#pragma unroll
        for (int g = 0; g < 4; g++) ldsm4t(a[g][i][0], a[g][i][1], a[g][i][2], a[g][i][3], stg + ((g * 16) ^ sw) + i * 2048);
#pragma unroll
    for (int e = 0; e < 16; e++) cs[e >> 2][e & 3] = 0.f;
#pragma unroll
    for (int i = 0; i < 4; i++)
#pragma unroll
        for (int g = 0; g < 4; g++) mma_bf16(cs[g], a[g][i][0], a[g][i][1], a[g][i][2], a[g][i][3], 0x3f803f80u, 0x3f803f80u);
    const int q = lane & 3;
    sts32(red + lane * 16 + pw * 4, __float_as_uint(q == 0 ? cs[0][0] + cs[0][2] : q == 1 ? cs[1][0] + cs[1][2] : q == 2 ? cs[2][0] + cs[2][2] : cs[3][0] + cs[3][2]));
    bar_sync(bar_id, 128);
    float t0, t1, t2, t3;
    asm volatile("ld.shared.v4.f32 {%0,%1,%2,%3}, [%4];" : "=f"(t0), "=f"(t1), "=f"(t2), "=f"(t3) : "r"(red + lane * 16));
    t0 = ((t0 + t1) + (t2 + t3)) * (-1.0f / 512);
    const uint32_t nm = pack_bf16(t0, t0);
#pragma unroll
    for (int g = 0; g < 4; g++) {
        const uint32_t m = __shfl_sync(0xffffffffu, nm, g, 4);
#pragma unroll
        for (int i = 0; i < 4; i++) {
#pragma unroll
            for (int e = 0; e < 4; e++) asm("add.rn.bf16x2 %0, %0, %1;" : "+r"(a[g][i][e]) : "r"(m));
            stsm4(so + (i >> 1) * 4096 + g * 1024 + (i & 1) * 512 + lane * 16, a[g][i][0], a[g][i][1], a[g][i][2], a[g][i][3]);
        }
    }
    fence_async_smem();
    __syncwarp();
    mbar_wait(gate);
#pragma unroll 1
    for (int i = 0; i < (u < 64 ? 4 : 8); i++) {
        const uint32_t o = __shfl_sync(0xffffffffu, off, i);
        if (o != ~0u && elect()) asm volatile("cp.async.bulk.global.shared::cta.bulk_group [%0], [%1], 2048;" ::"l"(S->w1p + o), "r"(so + (i & 3) * 2048) : "memory");
    }
    asm volatile("cp.async.bulk.commit_group;" ::: "memory");
    asm volatile("cp.async.bulk.wait_group 0;" ::: "memory");
    __syncwarp();
    bar_sync(bar_id, 128);
    if (pw == 3 && lane < 2) {
        red_release(&S->wcnt[j][p], 1);
    }
    __syncwarp();
}
struct Params { const bf16 *lar, *aim, *cr, *ci; GTab* gt; const bf16 *x, *ldt, *dsk; Scratch* s; const bf16* wd; bf16* out; int late; };

__global__ void __cluster_dims__(2, 1, 1) __launch_bounds__(384, 1)
fused_kernel(const Params P, const __grid_constant__ CUtensorMap tm_x, const __grid_constant__ CUtensorMap tm_wg, const __grid_constant__ CUtensorMap tm_wu,
             const __grid_constant__ CUtensorMap tm_wd64, const __grid_constant__ CUtensorMap tm_wd48) {
    extern __shared__ __align__(1024) unsigned char smem[];
    if (threadIdx.x < 32 && blockIdx.x < 128) {
        const uint32_t o = blockIdx.x * 512 + threadIdx.x * 16;
        asm volatile("prefetch.global.L2 [%0];" ::"l"(P.lar + o)); asm volatile("prefetch.global.L2 [%0];" ::"l"(P.aim + o));
        asm volatile("prefetch.global.L2 [%0];" ::"l"(P.cr + o)); asm volatile("prefetch.global.L2 [%0];" ::"l"(P.ci + o));
    }
    const uint32_t sb = __shfl_sync(0xffffffffu, s2u(smem), 0), bar = sb + SM_BAR;
    const int tid = threadIdx.x, warp = __shfl_sync(0xffffffffu, tid >> 5, 0), lane = tid & 31;
    const int rank = blockIdx.x & 1;
    const int c = blockIdx.x;
    bf16* const out = P.out;
    init_bars(bar, warp);
#define FIRST (((c >> 1) ^ c) & 1)
#define UNIT (FIRST ? c >> 1 : (c < P.late ? 64 + (c >> 1) : -1))
    if (warp == 11 && c < 128) {
        asm volatile("bar.arrive 0, 384;" ::: "memory");
        if (elect()) {
            constexpr uint32_t PB = 4 * SLOT + CV_PAR;
            mbar_expect(bar + B_PAR * 8, 4096 + 32);
            bulk_g2s(sb + PB, P.lar + c * 512, 1024, bar + B_PAR * 8);
            bulk_g2s(sb + PB + SLOT, P.aim + c * 512, 1024, bar + B_PAR * 8);
            bulk_g2s(sb + PB + 2 * SLOT, P.cr + c * 512, 1024, bar + B_PAR * 8);
            bulk_g2s(sb + PB + 3 * SLOT, P.ci + c * 512, 1024, bar + B_PAR * 8);
            bulk_g2s(sb + PB + 1024, P.ldt + (c >> 1) * 8, 16, bar + B_PAR * 8);
            bulk_g2s(sb + PB + 1040, P.dsk + (c >> 1) * 8, 16, bar + B_PAR * 8);
            mbar_expect(bar + B_GT * 8, sizeof(GTab));
            bulk_g2s(sb + SM_GT, P.gt, sizeof(GTab), bar + B_GT * 8);
            if (XDELAY) { const uint32_t t0 = clk32(); while (clk32() - t0 < XDELAY) {} }
            mbar_expect(bar + B_ROW * 8, 16384);
#pragma unroll
            for (int q = 0; q < 4; q++) bulk_g2s(sb + (4 + q) * SLOT + CV_X, P.x + (size_t)(c * 16 + q * 4) * 512, 4096, bar + B_ROW * 8);
        }
        __syncwarp();
        asm volatile("barrier.cluster.wait.aligned;" ::: "memory");
        if (elect()) {
#pragma unroll 1
            for (int q = FIRST ? 5 : 0; q < (FIRST ? 8 : 5); q++) {
                const int bx = (q + (c >> 1)) & 7;
                asm volatile("cp.async.bulk.tensor.2d.shared::cluster.global.mbarrier::complete_tx::bytes.multicast::cluster [%0], [%1, {%3, %4}], [%2], %5;"
                             ::"r"(sb + bx * 4096), "l"(&tm_x), "r"(bar + B_X * 8), "r"((c >> 1) * 8), "r"(bx * 256), "h"((uint16_t)3) : "memory");
            }
            if (UNIT >= 0) load_unit(UNIT, sb + 2 * SLOT, bar + B_W * 8, &tm_wg, &tm_wu);
        }
        __syncwarp();
    } else {
        asm volatile("bar.sync 0, 384;" ::: "memory");
    }

    if (warp >= 8 && c < 128) {
        const int pw = warp - 8, t128 = tid - 256;
        if (t128 == 96) mbar_expect(bar + B_ROLE * 8, 4);
        if (t128 < 40 && t128 != B_XREADY) {
            const int s = t128;
            uint32_t bytes = s < 16 ? 16384 : 12288;
            if (s < 4 || (s >= 4 + CV && s < 8 + CV) || (s >= 26 && s < 32)) bytes = 32768;
            if (s == 24 || s == 25) bytes = 16384;
            if (s == B_XFULL || s == B_XFULL + 2) bytes = 8192 + 512;
            if (s == 33) bytes = 3 * 24576;
            if (s == B_CS) bytes = 1024;
            mbar_expect(bar + s * 8, bytes);
        }
        mbar_wait(bar + B_GT * 8);
        const uint32_t epoch = lds32(sb + SM_GT), ep1 = epoch + 1;
        int pref = -1;
        uint32_t old = ep1;
        if (t128 == 64 && rank == 0) {
            pref = preferred_slot();
            if (pref >= 0) asm volatile("atom.relaxed.gpu.global.exch.b32 %0, [%1], %2;" : "=r"(old) : "l"(&P.s->claim[pref]), "r"(ep1) : "memory");
        }
        __syncwarp();
        {
            const uint32_t ra = sb + (4 + pw) * SLOT + CV_X + ((lane >> 1) & 3) * 1024 + (((lane >> 3) ^ ((lane >> 1) & 3)) * 2 + (lane & 1)) * 16;
            {
                mbar_wait(bar + B_ROW * 8);
                mbar_wait(bar + B_KALU * 8);
                float g[4][4];
#pragma unroll
                for (int e = 0; e < 16; e++) g[e >> 2][e & 3] = 0.f;
#pragma unroll
                for (int i = 0; i < 8; i++) {
                    uint32_t a[4];
                    ldsm4n(a, ra + i * 128);
                    mma_bf16(g[(i & 1) * 2], a[0], 0x3f803f80u, a[1], 0x3f803f80u, a[0], a[1]);
                    mma_bf16(g[(i & 1) * 2 + 1], a[2], 0x3f803f80u, a[3], 0x3f803f80u, a[2], a[3]);
                }
#pragma unroll
                for (int e = 0; e < 4; e++) g[0][e] = (g[0][e] + g[1][e]) + (g[2][e] + g[3][e]);
                const float qq = g[0][0] + __shfl_down_sync(0xffffffffu, g[0][1], 4);
                const float m = (g[0][2] + g[0][3]) * (1.0f / 512), var = fmaxf(fmaf(-m, m, qq * (1.0f / 512)), 0.f);
                float sd, rs;
                asm("sqrt.approx.ftz.f32 %0, %1;" : "=f"(sd) : "f"(rbf(rbf(var) + 1e-5f)));
                asm("rcp.approx.ftz.f32 %0, %1;" : "=f"(rs) : "f"(rbf(sd)));
                const uint32_t tag = ~epoch & 1;
                const uint32_t w0 = (__float_as_uint(rs) & ~1u) | tag, w1 = __float_as_uint(-rbf(m));
                asm volatile("{ .reg .pred p; .reg .b64 v; setp.ne.b32 p, %3, 0; mov.b64 v, {%1,%2}; @p st.relaxed.gpu.global.b64 [%0], v; }"
                             ::"l"(P.s->stat + c * 16 + pw * 4 + (lane & 3)), "r"(w0), "r"(w1), "r"((int)(lane == 9 * (lane & 3))) : "memory");
            }
        }
        bar_sync(12, 128);
        if (t128 == 0) mbar_expect(bar + B_X * 8, 32768);
        if (pw != 3) asm volatile("barrier.cluster.wait.aligned;" ::: "memory");
#define SEND_ROLE(v) _Pragma("unroll") for (int r = 0; r < 2; r++) \
            asm volatile("st.async.weak.shared::cluster.mbarrier::complete_tx::bytes.b32 [%0], %1, [%2];" ::"r"(mapa(sb + SM_MISC, r)), "r"(v), "r"(mapa(bar + B_ROLE * 8, r)) : "memory")
        if (t128 == 64 && rank == 0) {
            if (old != ep1) { SEND_ROLE(pref); }
            asm volatile("red.relaxed.gpu.global.add.u32 [%0], 1;" ::"l"(&P.s->nstart[0]) : "memory");
        }
        __syncwarp();
        {
            if (UNIT >= 0) pack_unit(P.s, UNIT, sb + 2 * SLOT, sb + SM_CS, bar + B_W * 8, bar + B_PREP * 8, 11, pw, lane, sb);
        }
        __syncwarp();
        asm volatile("setmaxnreg.dec.sync.aligned.u32 %0;" ::"n"(504 - 2 * CREGS));
        if (pw == 2 && rank == 0 && __shfl_sync(0xffffffffu, old, 0) == ep1) {
            int it = 0, got = -1;
            while ((int)(ld_relaxed(&P.s->nstart[0]) - ep1 * 64) < 0 && ++it < SPIN_LIMIT) {}
#pragma unroll 1
            for (it = 0; it < 64 && got < 0; it++) {
                const uint32_t rot = c >> 1;
                const uint32_t f0 = __ballot_sync(0xffffffffu, ld_relaxed(&P.s->claim[(lane + rot) & 63]) != ep1);
                const uint32_t f1 = __ballot_sync(0xffffffffu, ld_relaxed(&P.s->claim[(lane + 32 + rot) & 63]) != ep1);
                if (!(f0 | f1)) break;
                const int k = ((f0 ? __ffs(f0) - 1 : 31 + __ffs(f1)) + rot) & 63;
                uint32_t o = 0;
                if (lane == 0) o = atomicExch(&P.s->claim[k], ep1);
                if (__shfl_sync(0xffffffffu, o, 0) != ep1) got = k;
            }
            if (lane == 0) { SEND_ROLE(got & 63); }
            __syncwarp();
        }
        FFN_ROLE();
        if (pw > 0) mbar_wait(bar + B_CONV * 8);
        if (pw == 0) {
            if (elect()) {
                const unsigned char* wsrc = P.s->w1p + (size_t)j * CHUNK_BYTES;
                mbar_wait(bar + B_PREP * 8);
#pragma unroll
                for (int s = 0; s < 24; s++) {
                    if (s == 0 || s == 16) {
                        int it = 0;
                        uint4 f;
                        do { f = ld_relaxed4(&P.s->wcnt[j][0]); }
                        while ((s ? (int)(f.z - ep1 * (cb == 3 ? 4 : 6)) : ((int)(f.x - ep1 * 8) | (int)(f.y - ep1 * 8))) < 0 && ++it < SPIN_LIMIT);
                        asm volatile("fence.acquire.gpu;" ::: "memory");
                        fence_async_global();
                    }
                    if (s >= 6) mbar_wait(bar + (B_DONE + s - 6) * 8);
                    if (s == NPRE) mbar_wait(bar);
                    const uint32_t off = s >= 16 ? 65536 + s * 12288 : (s < 4 || s >= 8 + CV ? s : (s >= 4 + CV ? s - CV : s + 4)) * 16384;
                    bulk_g2s(sb + (8 + s % 6) * SLOT, wsrc + off, s < 16 ? 16384 : 12288, bar + s * 8);
                }
            }
        } else if (pw == 3) {
            if (elect()) {
                mbar_wait(bar + B_PREP * 8);
                asm volatile("cp.async.bulk.prefetch.L2.global [%0], %1;" ::"l"(P.wd + c * 4 * F_), "r"(8 * F_) : "memory");
                asm volatile("prefetch.tensormap [%0];" ::"l"(&tm_wd64) : "memory");
                asm volatile("prefetch.tensormap [%0];" ::"l"(&tm_wd48) : "memory");
                const int ckeep = cb * 128 + rank * 64, csend = ckeep ^ 64;
#pragma unroll
                for (int s = 24; s < 36; s++) {
                    const int p = s < 26 ? s - 24 : (s < 29 ? 0 : (s < 32 ? 1 : 2));
                    const int r = s < 26 || s == 32 ? 3 : (s < 32 ? (s - 26) % 3 : s - 33);
                    const int row = fcol(rank * 4 + (r == 3 ? cb : (r < cb ? r : r + 1)), p);
                    const int wslot = (s - 24) & 7;
                    mbar_wait(bar + (B_DONE + s - 8 + (s > 32)) * 8);
                    tma2d(sb + wslot * SLOT, p < 2 ? &tm_wd64 : &tm_wd48, bar + (s < 33 ? s : 33) * 8, ckeep, row);
                    tma2d(sb + wslot * SLOT + (p < 2 ? 8192 : 6144), p < 2 ? &tm_wd64 : &tm_wd48, bar + (s < 33 ? s : 33) * 8, csend, row);
                }
            }
        } else if (pw == 1) {
            if (elect()) {
#pragma unroll 1
                for (int wv = 0; wv < 2; wv++) {
                    if (wv) mbar_wait(bar + (B_CONV + 1) * 8);
                    const uint32_t target = ep1 * 32;
                    int it = 0;
                    uint4 f;
                    do { f = ld_relaxed4(&P.s->hcnt[rb][wv * 4]); }
                    while (((int)(f.x - target) | (int)(f.y - target) | (int)(f.z - target) | (int)(f.w - target)) < 0 && ++it < SPIN_LIMIT);
                    asm volatile("fence.acquire.gpu;" ::: "memory");
                    fence_async_global();
#pragma unroll
                    for (int i = 0; i < 4; i++) bulk_g2s(sb + (wv * 4 + i) * SLOT, P.s->hT + (size_t)(rb * 8 + wv * 4 + i) * SLOT, SLOT, bar + (wv * (4 + CV) + i) * 8);
                }
                if (c == 0) asm volatile("st.relaxed.gpu.global.u32 [%0], %1;" ::"l"(&P.gt->epoch), "r"(ep1) : "memory");
#pragma unroll
                for (int p = 0; p < 3; p++) {
                    int it = 0;
                    uint4 f;
                    do { f = ld_relaxed4(&P.s->acthint[rb * 2 + rank][p][0]); }
                    while (((f.x ^ ep1) | (f.y ^ ep1) | (f.z ^ ep1) | (f.w ^ ep1)) && ++it < SPIN_LIMIT);
#pragma unroll
                    for (int r = 0; r < 3; r++) {
                        const int s = 26 + p * 3 + r + (p == 2);
                        mbar_wait(bar + (B_DONE + s - ALEAD) * 8);
                        bulk_g2s(sb + ((s < 32 ? s - 24 : s - 31) + 6) * SLOT, &P.s->act[rb * 8 + rank * 4 + (r < cb ? r : r + 1)][p * 4][0], p < 2 ? 16384 : 12288, bar + (s < 33 ? s : 33) * 8);
                    }
                }
            }
        } else if (pw == 2) {
            if (lane < 16) {
                mbar_wait(bar + (B_CONV + 1) * 8);
                red_release(&P.s->hcnt[lane][4 + (c >> 5)], 1);
            }
            __syncwarp();
            if (elect()) {
                {
#pragma unroll 1
                    for (int p = 0; p < 3; p++) {
                        mbar_wait(bar + (B_STORED + p) * 8);
                        asm volatile("st.relaxed.gpu.global.u32 [%0], %1;" ::"l"(&P.s->acthint[rb * 2 + rank][p][cb]), "r"(ep1) : "memory");
                    }
                    mbar_wait(bar + (B_DONE + 29) * 8);
                    mbar_arrive_pair(mapa(bar + B_XREADY * 8, rank ^ 1));
                }
            }
        }
        __syncwarp();
    } else if (c < 128) {
        const int wg = warp >> 2, w = warp & 3;
        uint32_t tag;
        {
            const int chl = warp >> 1, half = warp & 1;
            const uint32_t cv = sb + (4 + chl) * SLOT;
            int tt = half * 32 + lane;
            asm volatile("" : "+r"(tt));
            if (tt < 25) sts128(tt < 24 ? cv + tt * 16 : cv + CV_KD + KD_ZERO, 0, 0, 0, 0);
            const uint32_t tb = sb + 8 * SLOT + warp * (42 * 272);
            float kscale, dskn;
            {
                mbar_wait(bar + B_PAR * 8);
                const uint32_t pa = sb + 4 * SLOT + CV_PAR + tid * 4;
                const uint32_t p_la = lds32(pa), p_ai = lds32(pa + SLOT), p_cr = lds32(pa + 2 * SLOT), p_ci = lds32(pa + 3 * SLOT);
                const uint32_t po = pa + (half ? -128 : 128), o_cr = lds32(po + 2 * SLOT), o_ci = lds32(po + 3 * SLOT);
                const uint32_t pd = sb + 4 * SLOT + CV_PAR + 1024 + (rank * 4 + chl) * 2;
                const float ldt = bf_lo(lds16(pd)), dsk = bf_lo(lds16(pd + 16));
                const float dt = rbf(expf(ldt));
                uint32_t mx = __vmaxu2(__vmaxu2(p_cr & 0x7fff7fffu, p_ci & 0x7fff7fffu), __vmaxu2(o_cr & 0x7fff7fffu, o_ci & 0x7fff7fffu));
                mx = __reduce_max_sync(0xffffffffu, max(mx << 16, mx & 0xffff0000u));
                kscale = rbf(fmaxf(fmaxf(2.0f * dt * __uint_as_float(mx), fabsf(dsk) * (1.0f / 1024)), 1e-30f));
                float kinv; asm("rcp.approx.ftz.f32 %0, %1;" : "=f"(kinv) : "f"(kscale));
                const float cn = 2.0f * dt * kinv;
                dskn = dsk * kinv;
                uint32_t ta = tb + lane * 8;
                cf z1[2], z8[2], z256[2], ch[2][3];
                uint32_t mu[2][4], mr[2][4];
#pragma unroll
                for (int m = 0; m < 2; m++) {
                    const float la = m ? bf_hi(p_la) : bf_lo(p_la), om = (m ? bf_hi(p_ai) : bf_lo(p_ai)) * dt;
                    float ea; asm("ex2.approx.ftz.f32 %0, %1;" : "=f"(ea) : "f"(la * 1.4426950408889634f));
                    const float al2 = rbf(ea) * dt * -1.4426950408889634f;
                    z1[m] = cpow(al2, -om, 1.f);
                    const cf z64 = cpow(al2, om, 64.f), z128 = csq(z64, 2.f), z2 = csq(z1[m], 2.f), z4 = csq(z2, 2.f);
                    z8[m] = csq(z4, -2.f);
                    z256[m] = csq(z128, -2.f);
                    mu[m][0] = pack_f16(z64.x, z64.y); mr[m][0] = pack_f16(-z64.y, z64.x);
                    mu[m][1] = pack_f16(z256[m].x, z256[m].y); mr[m][1] = pack_f16(-z256[m].y, z256[m].x);
                    mu[m][2] = pack_f16(z4.x, z4.y); mr[m][2] = pack_f16(-z4.y, z4.x);
                    mu[m][3] = pack_f16(z128.x, z128.y); mr[m][3] = pack_f16(-z128.y, z128.x);
                    ch[m][0] = {1.f, 0.f};
                    ch[m][1] = {(m ? bf_hi(p_cr) : bf_lo(p_cr)) * cn, (m ? bf_hi(p_ci) : bf_lo(p_ci)) * -cn};
                    ch[m][2] = cmul(ch[m][1], z256[m]);
                }
                sts64(ta + 40 * 272, mu[0][3], mu[1][3]);
                sts64(ta + 41 * 272, mr[0][3], mr[1][3]);
#pragma unroll 1
                for (int i2 = 0; i2 < 4; i2++) {
#pragma unroll
                    for (int i = 0; i < 2; i++) {
                        const uint32_t b0 = pack_f16(ch[0][0].x, ch[0][0].y), b1 = pack_f16(ch[1][0].x, ch[1][0].y);
                        const uint32_t a0 = pack_f16(ch[0][1].x, ch[0][1].y), a1 = pack_f16(ch[1][1].x, ch[1][1].y);
                        sts64(ta, b0, b1);
                        sts64(ta + 8 * 272, hcmul(b0, mu[0][0], mr[0][0]), hcmul(b1, mu[1][0], mr[1][0]));
                        sts64(ta + 16 * 272, a0, a1);
                        if (i == 0) sts64(ta + 24 * 272, hcmul(a0, mu[0][1], mr[0][1]), hcmul(a1, mu[1][1], mr[1][1]));
                        sts64(ta + 32 * 272, pack_f16(ch[0][2].x, ch[0][2].y), pack_f16(ch[1][2].x, ch[1][2].y));
#pragma unroll
                        for (int m = 0; m < 2; m++) { ch[m][0] = cmul(ch[m][0], z8[m]); ch[m][1] = cmul(ch[m][1], z1[m]); ch[m][2] = cmul(ch[m][2], z256[m]); }
                        ta += 272;
                    }
                }
#pragma unroll
                for (int r = 0; r < 2; r++) {
                    uint32_t v0, v1;
                    asm volatile("ld.shared.v2.u32 {%0,%1}, [%2];" : "=r"(v0), "=r"(v1) : "r"(ta + (25 + r) * 272));
                    sts64(ta + (17 + 2 * r) * 272, hcmul(v0, mu[0][2], mr[0][2]), hcmul(v1, mu[1][2], mr[1][2]));
                }
            }
            __syncwarp();
            if (lane == 0) mbar_arrive(bar + B_KALU * 8);
            uint32_t band2[4], band3[4], kv[20];
            uint4 st[4];
#define STAT_LOAD() _Pragma("unroll") for (int q = 0; q < 4; q++) st[q] = ld_relaxed2x64((const uint4*)P.s->stat + q * 256 + tid)
            {
                float kd[2][3][4];
#pragma unroll
                for (int i = 0; i < 24; i++) (&kd[0][0][0])[i] = 0.f;
                const uint32_t am = tb + 40 * 272 + (lane >> 3) * 16, ab = tb + (16 + (lane & 7)) * 272 + (lane >> 3) * 16;
                const uint32_t aa = tb + (lane & 15) * 272 + (lane >> 4) * 16;
#pragma unroll 2
                for (int k2 = 0; k2 < 4; k2++) {
                    uint32_t bq[3][4], p[2][4], m[4], n[4];
                    ldsm4n(p[0], aa + k2 * 64); ldsm4n(m, am + k2 * 64); ldsm4n(n, am + 272 + k2 * 64); ldsm4n(p[1], aa + k2 * 64 + 32);
#pragma unroll
                    for (int nt = 0; nt < 3; nt++) ldsm4n(bq[nt], ab + nt * 8 * 272 + k2 * 64);
#pragma unroll
                    for (int kk = 0; kk < 2; kk++) {
                        uint32_t q[4];
#pragma unroll
                        for (int e = 0; e < 4; e++) q[e] = hcmul(p[kk][e], m[2 * kk + (e >> 1)], n[2 * kk + (e >> 1)]);
#pragma unroll
                        for (int nt = 0; nt < 3; nt++) {
                            mma_f32(kd[0][nt], p[kk][0], p[kk][1], p[kk][2], p[kk][3], bq[nt][2 * kk], bq[nt][2 * kk + 1]);
                            mma_f32(kd[1][nt], q[0], q[1], q[2], q[3], bq[nt][2 * kk], bq[nt][2 * kk + 1]);
                        }
                    }
                }
                const uint32_t xo = cv + CV_TAB + lane * 16;
#pragma unroll
                for (int nt = 0; nt < 3; nt++) {
                    float g[4];
#pragma unroll
                    for (int e = 0; e < 4; e++) { g[e] = half ? kd[0][nt][e] : kd[1][nt][e]; kd[0][nt][e] = half ? kd[1][nt][e] : kd[0][nt][e]; }
                    sts128(xo + half * 1536 + nt * 512, __float_as_uint(g[0]), __float_as_uint(g[1]), __float_as_uint(g[2]), __float_as_uint(g[3]));
                }
                mbar_wait(bar + B_GT * 8);
                uint32_t gi[10];
                asm volatile("ld.shared.v4.u32 {%0,%1,%2,%3}, [%4];" : "=r"(gi[0]), "=r"(gi[1]), "=r"(gi[2]), "=r"(gi[3]) : "r"(sb + GT_V + tt * 48));
                asm volatile("ld.shared.v4.u32 {%0,%1,%2,%3}, [%4];" : "=r"(gi[4]), "=r"(gi[5]), "=r"(gi[6]), "=r"(gi[7]) : "r"(sb + GT_V + tt * 48 + 16));
                asm volatile("ld.shared.v2.u32 {%0,%1}, [%2];" : "=r"(gi[8]), "=r"(gi[9]) : "r"(sb + GT_V + tt * 48 + 32));
                asm volatile("ld.shared.v4.u32 {%0,%1,%2,%3}, [%4];" : "=r"(band2[0]), "=r"(band2[1]), "=r"(band2[2]), "=r"(band2[3]) : "r"(sb + GT_BAND + (tt & 31) * 32));
                asm volatile("ld.shared.v4.u32 {%0,%1,%2,%3}, [%4];" : "=r"(band3[0]), "=r"(band3[1]), "=r"(band3[2]), "=r"(band3[3]) : "r"(sb + GT_BAND + 16 + (tt & 31) * 32));
                tag = ~lds32(sb + SM_GT) & 1;
                bar_sync(1 + chl, 64);
                if (tt == 0) kd[0][0][0] += dskn;
                const uint32_t kdb = cv + CV_KD + (half * 8 + (tt >> 2)) * KD_PITCH + (tt & 3) * 4;
                float t[3][4];
#pragma unroll
                for (int nt = 0; nt < 3; nt++)
                    asm volatile("ld.shared.v4.f32 {%0,%1,%2,%3}, [%4];" : "=f"(t[nt][0]), "=f"(t[nt][1]), "=f"(t[nt][2]), "=f"(t[nt][3]) : "r"(xo + (half ^ 1) * 1536 + nt * 512));
#pragma unroll
                for (int nt = 0; nt < 3; nt++) {
                    sts32(kdb + nt * 16, pack_f16(kd[0][nt][0] + t[nt][0], kd[0][nt][1] + t[nt][1]));
                    sts32(kdb + nt * 16 + 8 * KD_PITCH, pack_f16(kd[0][nt][2] + t[nt][2], kd[0][nt][3] + t[nt][3]));
                }
                bar_sync(1 + chl, 64);
#pragma unroll
                for (int e = 0; e < 20; e++) kv[e] = lds16(cv + CV_KD + ((e & 1) ? gi[e >> 1] >> 16 : gi[e >> 1] & 0xffffu));
#define TAB_STORE() _Pragma("unroll") for (int g = 0; g < 4; g++) \
                    sts128(cv + CV_TAB + tt * 16 + g * 1024, __byte_perm(kv[5 * g + 1], kv[5 * g], 0x5410), __byte_perm(kv[5 * g + 2], kv[5 * g + 1], 0x5410), \
                           __byte_perm(kv[5 * g + 3], kv[5 * g + 2], 0x5410), __byte_perm(kv[5 * g + 4], kv[5 * g + 3], 0x5410))
            }
            {
                const int o = (tt >> 2) & 1;
                const uint32_t xa = sb + tid * 32 + rank * 8;
                const uint32_t sel0 = o ? 0x1054 : 0x5410, sel1 = o ? 0x3276 : 0x7632;
                uint32_t xv[4][4];
                mbar_wait(bar + B_X * 8);
                STAT_LOAD();
#pragma unroll
                for (int q = 0; q < 4; q++) {
                    asm volatile("ld.shared.v2.u32 {%0,%1}, [%2];" : "=r"(xv[q][0]), "=r"(xv[q][1]) : "r"(xa + q * 8192 + o * 16));
                    asm volatile("ld.shared.v2.u32 {%0,%1}, [%2];" : "=r"(xv[q][2]), "=r"(xv[q][3]) : "r"(xa + q * 8192 + (o ^ 1) * 16));
                }
                TAB_STORE();
#pragma unroll
                for (int q = 0; q < 4; q++) {
                    const uint32_t a0 = xv[q][0], a1 = xv[q][1], b0 = xv[q][2], b1 = xv[q][3];
                    xv[q][0] = __byte_perm(a0, b0, sel0); xv[q][1] = __byte_perm(a0, b0, sel1);
                    xv[q][2] = __byte_perm(a1, b1, sel0); xv[q][3] = __byte_perm(a1, b1, sel1);
                }
                const uint32_t c0 = sb + 4 * SLOT + CV_U + tid * 4;
                int it = 0;
                while (__builtin_expect(__any_sync(0xffffffffu, tag_bad(st[0].x, st[0].z, st[1].x, st[1].z, tag) | tag_bad(st[2].x, st[2].z, st[3].x, st[3].z, tag)), 0) && ++it < SPIN_LIMIT) {
                    STAT_LOAD();
                }
#pragma unroll
                for (int q = 0; q < 4; q++) {
                    const uint32_t nm = __byte_perm(st[q].y, st[q].w, 0x7632);
#pragma unroll
                    for (int h = 0; h < 4; h++) {
                        asm("add.rn.bf16x2 %0, %0, %1;" : "+r"(xv[q][h]) : "r"(nm));
                        sts32(c0 + h * SLOT + q * 1024, pack_f16(bf_lo(xv[q][h]) * __uint_as_float(st[q].x), bf_hi(xv[q][h]) * __uint_as_float(st[q].z)));
                    }
                }
#pragma unroll
                for (int h = 0; h < 4; h++) sts128(sb + (4 + h) * SLOT + CV_X + tid * 16, xv[0][h], xv[1][h], xv[2][h], xv[3][h]);
                bar_sync(5, 256);
                if (lane == 0) mbar_arrive(bar + B_PREP * 8);
            }
            {
                const int up = half ^ wg, k = (wg * 256 + c * 2 + (chl & 1)) ^ (wg * 4);
                unsigned char* hp = P.s->hT + (k >> 6) * SLOT + (k & 63) * 128 + (((lane >> 2) ^ (k & 7)) << 4) + (lane & 3) * 4;
                if (wg == 1) mbar_wait(bar + (B_ORDER + w) * 8);
                uint32_t cvv = cv;
                asm volatile("" : "+r"(cvv)::"memory");
                const uint32_t rel = bar + (B_ORDER + warp) * 8;
                if (up) conv_tiles<SPLIT, 16 - SPLIT>(cvv, lane, rel, band2, band3, hp, kscale); else conv_tiles<0, SPLIT>(cvv, lane, rel, band2, band3, hp, kscale);
                __syncwarp();
                if (lane == 0) mbar_arrive2(bar + (B_CONV + wg) * 8);
                if (tid < 16) {
                    mbar_wait(bar + B_CONV * 8);
                    red_release(&P.s->hcnt[lane][c >> 5], 1);
                }
                __syncwarp();
                if (wg == 0) mbar_wait(bar + (B_ORDER + 4 + w) * 8);
            }
        }
        asm volatile("setmaxnreg.inc.sync.aligned.u32 %0;" ::"n"(CREGS));
        asm volatile("barrier.cluster.wait.aligned;" ::: "memory");
        FFN_ROLE();
        {
#define WAITP(s) mbar_wait(bar + (s) * 8)
#define WAITC(s) mbar_wait_cluster(bar + (s) * 8)
        float accA[64], accB[64];
        uint32_t act0[16], act1[16], act2[12], resid[16];
        RowC c0, c1;
        float sc0, sc1;
        uint4* const act_g = &P.s->act[rb * 8 + j][0][tid];
        uint32_t ldsm_a = sb + wg * 8192 + rank * 4096 + ((lane >> 4) * 8 + (lane & 7)) * 128 + (((2 * w + ((lane >> 3) & 1)) ^ (lane & 7)) << 4);
        const uint32_t dA = __shfl_sync(0xffffffffu, desc_lo(sb + wg * 8192, 0), 0);
        const uint32_t dB = __shfl_sync(0xffffffffu, desc_lo(sb, 128), 0);
#define STEP_DONE(s) do { wg_commit(); wg_wait<1>(); if ((s) <= 30 && lane == 0) mbar_arrive(bar + (B_DONE + (s) - 1) * 8);  } while (0)
#define HINT(p) mbar_arrive(bar + (B_STORED + (p)) * 8)
#define GEGLU(NG, ACC, ACT, q, ks0) do { geglu_group<NG>(ACC, q, c0, c1, ACT[2 * (q)], ACT[2 * (q) + 1]); \
            if ((q) & 1) { ACT[2 * (q) - 2] = (ACT[2 * (q) - 2] & ~1u) | tag; \
                st_relaxed4(act_g + ((ks0) + (q) / 2) * 256, ACT[2 * (q) - 2], ACT[2 * (q) - 1], ACT[2 * (q)], ACT[2 * (q) + 1]); } } while (0)

        float s0 = 0, q0 = 0, s1 = 0, q1 = 0;
#pragma unroll
        for (int i = 0; i < 64; i++) accA[i] = 0.f;
        pin(accA);
        asm volatile("" : "+r"(ldsm_a));
#define PASS0_LOOP(S0, KB0) _Pragma("unroll 1") for (int i = 0; i < 4; i++) { \
            uint32_t f[8]; \
            WAITP((S0) + i); \
            wg_fence(); \
            const uint32_t la = dA + ((KB0) + i) * (SLOT >> 4), lb = dB + (8 + (S0) % 6 + i) * (SLOT >> 4); \
            _Pragma("unroll") for (int ks = 0; ks < 4; ks++) wg128_ss_tn<HI_SW128, HI_NOSW, 1>(accA, la + ks * 128, lb + ks * 16); \
            wg_commit(); \
            ldsm4t(f[0], f[1], f[2], f[3], ldsm_a); ldsm4t(f[4], f[5], f[6], f[7], ldsm_a + 2048); \
            ldsm_a += SLOT; \
            wg_wait<1>(); \
            if (lane == 0 && (S0) + i > 0) mbar_arrive(bar + (B_DONE + (S0) + i - 1) * 8); \
            stats_acc(f, s0, q0, s1, q1); }
#define STAT_SEND() do { const bool hi_ = lane & 2, od_ = lane & 1; \
            const float a_ = (hi_ ? s1 : s0) + __shfl_xor_sync(0xffffffffu, hi_ ? s0 : s1, 2), b_ = (hi_ ? q1 : q0) + __shfl_xor_sync(0xffffffffu, hi_ ? q0 : q1, 2); \
            const float v_ = (od_ ? b_ : a_) + __shfl_xor_sync(0xffffffffu, od_ ? a_ : b_, 1); \
            asm volatile("st.async.weak.shared::cluster.mbarrier::complete_tx::bytes.f32 [%0], %1, [%2];" ::"r"(mapa(sb + SM_CS + tid * 4, rank ^ 1)), \
                         "f"(v_), "r"(mapa(bar + B_CS * 8, rank ^ 1)) : "memory"); \
            s0 = v_; } while (0)
        PASS0_LOOP(0, 0)
#pragma unroll
        for (int kb = 0; kb < 8; kb++) {
            const int s = kb < CV ? 4 + kb : 8 + kb;
            if (kb == CV) {
                PASS0_LOOP(4 + CV, 4)
                STAT_SEND();
            }
            WAITP(s);
            wg_fence();
#pragma unroll
            for (int ks = 0; ks < 4; ks++) {
                const uint32_t la = dA + ((kb * SLOT + ks * 2048) >> 4), lb = dB + (((8 + s % 6) * SLOT + ks * 256) >> 4);
                if (kb | ks) wg128_ss_tn<HI_SW128, HI_NOSW, 1>(accB, la, lb); else wg128_ss_tn<HI_SW128, HI_NOSW, 0>(accB, la, lb);
            }
            STEP_DONE(s);
            if (s == 8 + CV) { pin(accA);  }
            if (s == RES_STEP) {
                const int r = lane & 7, mi = lane >> 3, wv = (r >> 1) & 1, row = (4 * (mi >> 1) + 2 * (r >> 2) + (r & 1)) ^ (4 * wv);
#pragma unroll
                for (int v = 0; v < 4; v++)
                    ldsm4t(resid[4 * v], resid[4 * v + 1], resid[4 * v + 2], resid[4 * v + 3],
                           sb + (wv * 4 + cb) * SLOT + wg * 8192 + (32 * rank + 8 * v + row) * 128 + (((2 * w + (mi & 1)) ^ row) << 4));
            }
            if (s == RECV_STEP) {
                WAITC(B_CS);
                s0 += __uint_as_float(lds32(sb + SM_CS + tid * 4));
                ln_finish(__shfl_sync(0xffffffffu, s0, 0, 4), __shfl_sync(0xffffffffu, s0, 1, 4), c0, sc0);
                ln_finish(__shfl_sync(0xffffffffu, s0, 2, 4), __shfl_sync(0xffffffffu, s0, 3, 4), c1, sc1);
            }
#pragma unroll
            for (int q = 0; q < 8; q++) if (((SCHED0 >> (4 * q)) & 15) == s - 12) GEGLU(8, accA, act0, q, 0);
            if (s - 12 == (SCHED0 >> 28) && lane == 0) HINT(0);
        }
        float accC[48];
#pragma unroll
        for (int kb = 0; kb < 8; kb++) {
            const int s = 16 + kb;
            WAITP(s);
            wg_fence();
#pragma unroll
            for (int ks = 0; ks < 4; ks++) {
                const uint32_t la = dA + ((kb * SLOT + ks * 2048) >> 4), lb = dB + (((8 + s % 6) * SLOT + ks * 256) >> 4);
                if (kb | ks) wg96_ss_tn<HI_SW128, HI_NOSW, 1>(accC, la, lb); else wg96_ss_tn<HI_SW128, HI_NOSW, 0>(accC, la, lb);
            }
            STEP_DONE(s);
            if (kb == 0) { pin(accB);  }
#pragma unroll
            for (int q = 0; q < 8; q++) if (((SCHED0 >> (4 * q)) & 15) == s - 12) GEGLU(8, accA, act0, q, 0);
            if (s - 12 == (SCHED0 >> 28) && lane == 0) HINT(0);
#pragma unroll
            for (int q = 0; q < 8; q++) if (((SCHED1 >> (4 * q)) & 15) == kb) GEGLU(8, accB, act1, q, 4);
            if (kb == (SCHED1 >> 28) && lane == 0) HINT(1);
        }
        const uint32_t dW64 = dB + ((512 - 8) << 16), dW48 = dB + ((384 - 8) << 16);
        const uint32_t st = sb + 4 * SLOT + (tid >> 5) * 2048;
        uint4 fr[9][4];
#define FR_GET(n) do { const int s_ = 26 + (n) + ((n) >= 6), nk_ = (n) < 6 ? 4 : 3; \
            if (s_ <= 33) WAITP(s_); \
            _Pragma("unroll") for (int ks = 0; ks < nk_; ks++) \
                asm volatile("ld.shared.v4.u32 {%0,%1,%2,%3}, [%4];" : "=r"(fr[n][ks].x), "=r"(fr[n][ks].y), "=r"(fr[n][ks].z), "=r"(fr[n][ks].w) \
                             : "r"(sb + ((s_ < 32 ? s_ - 24 : s_ - 31) + 6) * SLOT + ks * 4096 + tid * 16)); } while (0)
        uint32_t err = 0;
        float nm0, nm1;
#define FR_CHECK(n) do { uint32_t x_, y_; \
            asm("lop3.b32 %0, %1, %2, %3, 0x7e;" : "=r"(x_) : "r"(fr[n][0].x), "r"(fr[n][1].x), "r"(tag)); \
            asm("lop3.b32 %0, %1, %2, %3, 0x7e;" : "=r"(y_) : "r"(fr[n][2].x), "r"(fr[n][(n) < 6 ? 3 : 2].x), "r"(tag)); \
            asm volatile("lop3.b32 %0, %0, %1, %2, 0xfe;" : "+r"(err) : "r"(x_), "r"(y_)); } while (0)
        pin(act0); pin(act1);
#pragma unroll
        for (int s = 24; s < 32; s++) {
            if (s < 26) WAITP(s); else FR_CHECK(s >= 26 ? s - 26 : 0);
            wg_fence();
#pragma unroll
            for (int ks = 0; ks < 4; ks++) {
                const uint32_t lb = dW64 + (((s - 24) * SLOT + ks * 2048) >> 4);
                const uint4 a = fr[s >= 26 ? s - 26 : 0][ks];
                if (s == 24 && ks == 0) wg128_rs_t<HI_SW128, 0>(accA, act0[0], act0[1], act0[2], act0[3], lb);
                else if (s == 24) wg128_rs_t<HI_SW128, 1>(accA, act0[4 * ks], act0[4 * ks + 1], act0[4 * ks + 2], act0[4 * ks + 3], lb);
                else if (s == 25) wg128_rs_t<HI_SW128, 1>(accA, act1[4 * ks], act1[4 * ks + 1], act1[4 * ks + 2], act1[4 * ks + 3], lb);
                else wg128_rs_t<HI_SW128, 1>(accA, a.x, a.y, a.z, a.w, lb);
            }
            STEP_DONE(s);
            if (s == 24) { pin(accC);  }
            if (s >= 25 && s < 31) FR_GET(s >= 25 && s < 31 ? s - 25 : 0);
#pragma unroll
            for (int q = 0; q < 6; q++) if (((SCHED2 >> (4 * q)) & 15) == s - 24) GEGLU(6, accC, act2, q, 8);
            if (s - 24 == (SCHED2 >> 20) && lane == 0) HINT(2);
            if (s == 28) {
                const float2* sp = P.s->stat + rb * 128 + (tid >> 5) * 16 + (lane >> 2);
                nm0 = __ldcg(&sp[0].y); nm1 = __ldcg(&sp[8].y);
            }
        }
        float accS[32], accK[32];
        const uint32_t dWx = dW48 + (cb == 3 ? (3 * SLOT) >> 4 : 0);
#define LAST_MMA(ACC, n, off) do { const int g_ = (n) / 3, ks_ = (n) % 3; \
            const uint32_t lb_ = ((n) == 2 ? dWx : dW48) + ((g_ * SLOT + ks_ * 2048 + (off)) >> 4); \
            const uint4 a_ = fr[5 + (g_ ? g_ : 1)][ks_]; \
            if ((n) == 0) wg64_rs_t<HI_SW128, 0>(ACC, act2[4 * ks_], act2[4 * ks_ + 1], act2[4 * ks_ + 2], act2[4 * ks_ + 3], lb_); \
            else if (g_ == 0) wg64_rs_t<HI_SW128, 1>(ACC, act2[4 * ks_], act2[4 * ks_ + 1], act2[4 * ks_ + 2], act2[4 * ks_ + 3], lb_); \
            else wg64_rs_t<HI_SW128, 1>(ACC, a_.x, a_.y, a_.z, a_.w, lb_); } while (0)
        WAITP(32);
        {
            asm volatile("" : "+r"(act2[0]), "+r"(act2[1]), "+r"(act2[2]), "+r"(act2[3]), "+r"(act2[4]), "+r"(act2[5]), "+r"(act2[6]), "+r"(act2[7])::"memory");
            wg_fence();
            LAST_MMA(accS, 0, 6144); LAST_MMA(accS, 1, 6144);
            wg_commit();
        }
        float base[32];
        {
#pragma unroll
            for (int i = 0; i < 32; i++) base[i] = ((i & 1) ? bf_hi(resid[i >> 1]) : bf_lo(resid[i >> 1])) - ((i & 2) ? nm1 : nm0);
            pin(base);
        }
        if (wg == 1) bar_sync(10, 256);
        FR_GET(6); FR_GET(7); FR_GET(8);
        FR_CHECK(6); FR_CHECK(7); FR_CHECK(8);
        if (wg == 0) asm volatile("bar.arrive 10, 256;" ::: "memory");
        if (cb == 3) { act2[8] = fr[8][2].x; act2[9] = fr[8][2].y; act2[10] = fr[8][2].z; act2[11] = fr[8][2].w; }
        asm volatile("" : "+r"(act2[8]), "+r"(act2[9]), "+r"(act2[10]), "+r"(act2[11])::"memory");
        if (wg == 1) bar_sync(7, 256);
        wg_fence();
#pragma unroll
        for (int n = 2; n < 11; n++) LAST_MMA(accS, n, 6144);
        wg_commit();
        asm volatile("bar.arrive %0, 256;" ::"r"(7 + wg) : "memory");
        WAITP(B_XREADY);
        wg_wait<0>();
        pin(accA); pin(accS);
        const uint32_t xb = sb + 5 * SLOT + tid * 16;
        {
            const uint32_t rx = mapa(xb, rank ^ 1), rbar = mapa(bar + (B_XFULL + 2 * wg) * 8, rank ^ 1);
#pragma unroll
            for (int i = 0; i < 32; i++) accS[i] += accA[32 + i];
#pragma unroll
            for (int v = 0; v < 4; v++)
                asm volatile("st.async.weak.shared::cluster.mbarrier::complete_tx::bytes.v4.b32 [%0], {%1,%2,%3,%4}, [%5];" ::"r"(rx + v * 4096),
                             "r"(pack_bf16(accS[8 * v], accS[1 + 8 * v])), "r"(pack_bf16(accS[2 + 8 * v], accS[3 + 8 * v])),
                             "r"(pack_bf16(accS[4 + 8 * v], accS[5 + 8 * v])), "r"(pack_bf16(accS[6 + 8 * v], accS[7 + 8 * v])), "r"(rbar) : "memory");
            asm volatile("st.async.weak.shared::cluster.mbarrier::complete_tx::bytes.b32 [%0], %1, [%2];" ::"r"(mapa(sb + SM_CS + tid * 4, rank ^ 1)), "r"(err), "r"(rbar) : "memory");
        }
        bar_sync(8 + wg, 256);
        wg_fence();
#pragma unroll
        for (int n = 0; n < 11; n++) LAST_MMA(accK, n, 0);
        wg_commit();
        if (wg == 0) asm volatile("bar.arrive 9, 256;" ::: "memory");
        {
            const int r = lane & 7, mi = lane >> 3;
            uint32_t x[16];
#pragma unroll
            for (int i = 0; i < 32; i++) {
                accA[i] = fmaf(accA[i], (i & 2) ? sc1 : sc0, base[i]);
            }
            wg_wait<0>();
            pin(accK);
#pragma unroll
            for (int i = 0; i < 32; i++) accA[i] = fmaf(accK[i], (i & 2) ? sc1 : sc0, accA[i]);
            WAITC(B_XFULL + 2 * wg);
#pragma unroll
            for (int v = 0; v < 4; v++)
                asm volatile("ld.shared.v4.u32 {%0,%1,%2,%3}, [%4];" : "=r"(x[4 * v]), "=r"(x[4 * v + 1]), "=r"(x[4 * v + 2]), "=r"(x[4 * v + 3]) : "r"(xb + v * 4096));
            err |= lds32(sb + SM_CS + tid * 4) | FORCE_REDO;
#pragma unroll
            for (int e = 0; e < 16; e++) {
                const float sc = (e & 1) ? sc1 : sc0;
                x[e] = pack_bf16(fmaf(bf_lo(x[e]), sc, accA[2 * e]), fmaf(bf_hi(x[e]), sc, accA[2 * e + 1]));
            }
            __nv_bfloat16* op = out + (size_t)(rb * 128 + (tid >> 5) * 16 + mi) * 512 + cb * 128 + rank * 64 + r * 8;
#pragma unroll 1
            while (true) {
                __syncwarp();
#pragma unroll
                for (int v = 0; v < 4; v++) stsm4(st + ((mi & 1) * 8 + r) * 128 + (((2 * v + (mi >> 1)) ^ r) << 4), x[4 * v], x[4 * v + 1], x[4 * v + 2], x[4 * v + 3]);
                __syncwarp();
#pragma unroll
                for (int v = 0; v < 4; v++)
                    asm volatile("ld.shared.v4.u32 {%0,%1,%2,%3}, [%4];" : "=r"(x[4 * v]), "=r"(x[4 * v + 1]), "=r"(x[4 * v + 2]), "=r"(x[4 * v + 3])
                                 : "r"(st + (v * 4 + mi) * 128 + ((r ^ ((v * 4 + mi) & 7)) << 4)));
#pragma unroll
                for (int v = 0; v < 4; v++) {
                    *(uint4*)(op + v * 4 * 512) = make_uint4(x[4 * v], x[4 * v + 1], x[4 * v + 2], x[4 * v + 3]);
                }
                if (!__any_sync(0xffffffffu, err & 1)) break;
                err = 0;
                float d[8][4];
#pragma unroll
                for (int i = 0; i < 32; i++) d[i >> 2][i & 3] = 0.f;
#pragma unroll 1
                for (int n = 0; n < 87; n++) {
                    if (n == 43) continue;
                    const int jj = n / 11, ks = n - 11 * jj;
                    uint4 a;
                    int it = 0;
                    do { a = ld_relaxed128(&P.s->act[rb * 8][n][tid]); } while (__any_sync(0xffffffffu, (a.x ^ tag) & 1) && ++it < SPIN_LIMIT);
                    const unsigned short* wp = (const unsigned short*)P.wd + (fcol(jj, ks >> 2) + (ks & 3) * 16 + (lane & 3) * 2) * 512 + cb * 128 + rank * 64 + (lane >> 2);
#pragma unroll
                    for (int q = 0; q < 8; q++)
                        mma_bf16(d[q], a.x, a.y, a.z, a.w, wp[q * 8] | ((uint32_t)wp[q * 8 + 512] << 16), wp[q * 8 + 4096] | ((uint32_t)wp[q * 8 + 4608] << 16));
                }
#pragma unroll
                for (int e = 0; e < 16; e++) {
                    const float sc = (e & 1) ? sc1 : sc0;
                    x[e] = pack_bf16(fmaf(d[e >> 1][(e & 1) * 2], sc, base[2 * e]), fmaf(d[e >> 1][(e & 1) * 2 + 1], sc, base[2 * e + 1]));
                }
            }
        }
        }
    } else {
        if (warp == 0 && elect()) {
            const uint32_t t0 = clk32();
            while (clk32() - t0 < EXTRA_DELAY) {}
#pragma unroll 1
            for (int i = 0; i < 6; i++) if (c - 64 + 4 * i < 86) load_unit(c - 64 + 4 * i, sb + i * 32768, bar + i * 8, &tm_wg, &tm_wu);
        }
        __syncwarp();
#pragma unroll 1
        for (int i = warp >> 2; i < 6; i += 3)
            if (c - 64 + 4 * i < 86) pack_unit(P.s, c - 64 + 4 * i, sb + i * 32768, sb + 12 * SLOT + i * 512, bar + i * 8, bar + i * 8, 1 + (warp >> 2), warp & 3, lane, sb);
    }
}

typedef CUresult (*EncFn)(CUtensorMap*, CUtensorMapDataType, cuuint32_t, void*, const cuuint64_t*, const cuuint64_t*, const cuuint32_t*, const cuuint32_t*,
                          CUtensorMapInterleave, CUtensorMapSwizzle, CUtensorMapL2promotion, CUtensorMapFloatOOBfill);

extern "C" void kernel_launch(void* const* d_in, const int* in_sizes, int n_in, void* d_out, int out_size) {
    static EncFn enc = nullptr;
    static void *p_gt = nullptr, *p_scr = nullptr;
    static int grid = GRID;
    if (!enc) {
        cudaGetSymbolAddress(&p_gt, g_gtab);
        cudaGetSymbolAddress(&p_scr, g_scr);
        void* fn = nullptr; cudaDriverEntryPointQueryResult qr;
        cudaGetDriverEntryPoint("cuTensorMapEncodeTiled", &fn, cudaEnableDefault, &qr);
        enc = (EncFn)fn;
        cudaFuncSetAttribute(fused_kernel, cudaFuncAttributeMaxDynamicSharedMemorySize, SMEM_BYTES);
        cudaLaunchConfig_t cfg = {};
        cfg.gridDim = dim3(GRID); cfg.blockDim = dim3(384); cfg.dynamicSmemBytes = SMEM_BYTES;
        cudaLaunchAttribute at; at.id = cudaLaunchAttributeClusterDimension; at.val.clusterDim.x = 2; at.val.clusterDim.y = 1; at.val.clusterDim.z = 1;
        cfg.attrs = &at; cfg.numAttrs = 1;
        int ncl = 0;
        if (cudaOccupancyMaxActiveClusters(&ncl, fused_kernel, &cfg) != cudaSuccess || ncl * 2 < GRID) grid = 128;
        (void)cudaGetLastError();
    }
    CUtensorMap tmx, tmg, tmu, tm64, tm48;
    cuuint64_t str[1] = {1024}; cuuint32_t es[2] = {1, 1};
    cuuint64_t dw[2] = {512, F_};
    cuuint32_t b64[2] = {64, 64}, b48[2] = {64, 48};
    cuuint64_t dx[2] = {512, 2048}; cuuint32_t bx[2] = {8, 256};
    enc(&tmx, CU_TENSOR_MAP_DATA_TYPE_BFLOAT16, 2, d_in[0], dx, str, bx, es, CU_TENSOR_MAP_INTERLEAVE_NONE, CU_TENSOR_MAP_SWIZZLE_NONE, CU_TENSOR_MAP_L2_PROMOTION_NONE, CU_TENSOR_MAP_FLOAT_OOB_FILL_NONE);
    enc(&tm64, CU_TENSOR_MAP_DATA_TYPE_BFLOAT16, 2, d_in[10], dw, str, b64, es, CU_TENSOR_MAP_INTERLEAVE_NONE, CU_TENSOR_MAP_SWIZZLE_128B, CU_TENSOR_MAP_L2_PROMOTION_L2_128B, CU_TENSOR_MAP_FLOAT_OOB_FILL_NONE);
    enc(&tm48, CU_TENSOR_MAP_DATA_TYPE_BFLOAT16, 2, d_in[10], dw, str, b48, es, CU_TENSOR_MAP_INTERLEAVE_NONE, CU_TENSOR_MAP_SWIZZLE_128B, CU_TENSOR_MAP_L2_PROMOTION_L2_128B, CU_TENSOR_MAP_FLOAT_OOB_FILL_NONE);
    {
        cuuint64_t d4[4] = {F_, 2, 128, 2}, s4[3] = {F_ * 2, F_ * 8, F_ * 4}; cuuint32_t b4[4] = {32, 2, 128, 2}, e4[4] = {1, 1, 1, 1};
        enc(&tmg, CU_TENSOR_MAP_DATA_TYPE_BFLOAT16, 4, d_in[8], d4, s4, b4, e4, CU_TENSOR_MAP_INTERLEAVE_NONE, CU_TENSOR_MAP_SWIZZLE_64B, CU_TENSOR_MAP_L2_PROMOTION_NONE, CU_TENSOR_MAP_FLOAT_OOB_FILL_NONE);
        enc(&tmu, CU_TENSOR_MAP_DATA_TYPE_BFLOAT16, 4, d_in[9], d4, s4, b4, e4, CU_TENSOR_MAP_INTERLEAVE_NONE, CU_TENSOR_MAP_SWIZZLE_64B, CU_TENSOR_MAP_L2_PROMOTION_NONE, CU_TENSOR_MAP_FLOAT_OOB_FILL_NONE);
    }
    Params P = {(const bf16*)d_in[1], (const bf16*)d_in[2], (const bf16*)d_in[3], (const bf16*)d_in[4], (GTab*)p_gt, (const bf16*)d_in[0], (const bf16*)d_in[5],
                (const bf16*)d_in[6], (Scratch*)p_scr, (const bf16*)d_in[10], (bf16*)d_out, grid == 128 ? 44 : 0};
    fused_kernel<<<grid, 384, SMEM_BYTES>>>(P, tmx, tmg, tmu, tm64, tm48);
}
```
